```python
import torch

def _softmax(x, axis=-1):
    return torch.softmax(x, dim=axis)
def _gelu(x):
    return torch.nn.functional.gelu(x, approximate="tanh")
def _silu(x):
    return torch.nn.functional.silu(x)
def _sigmoid(x):
    return torch.sigmoid(x)
def _layernorm(x, axis=-1, eps=1e-5):
    m = x.mean(dim=axis, keepdim=True)
    v = x.var(dim=axis, keepdim=True, unbiased=False)
    return (x - m) / torch.sqrt(v + eps)
def _scatter_add(tgt, idx, src, axis=0):
    return tgt.clone().index_add_(axis, idx, src)
def _segment_sum(src, seg, n):
    out = torch.zeros((n,) + src.shape[1:], dtype=src.dtype)
    return out.index_add_(0, seg, src)
def _pad(x, pw):
    flat = tuple(v for pair in reversed(pw) for v in pair)
    return torch.nn.functional.pad(x, flat)

kernel_name = 'recurrent_scan__ssm_conv_h3__dense_activation_relu__prompt'

def setup_inputs():

    _w = (lambda a: (lambda t: t.to(torch.bfloat16) if t.is_floating_point() else t)(torch.as_tensor(a)))
    def _A_setup():
        B, S, D = 1, 2048, 640
        ks = 4
        return {
            "q": _w((lambda *s: torch.randn(*s, dtype=torch.bfloat16) * 0.05)(B, S, D)),
            "k": _w((lambda *s: torch.randn(*s, dtype=torch.bfloat16) * 0.2)(B, S, D)),
            "v": _w((lambda *s: torch.randn(*s, dtype=torch.bfloat16) * 0.2)(B, S, D)),
            "shift_k": _w((lambda *s: torch.randn(*s, dtype=torch.bfloat16) * 0.2)(D, ks) * 0.5),
            "ssm_k": _w((lambda *s: torch.randn(*s, dtype=torch.bfloat16) * 0.2)(D, S) * (1.0 / S ** 0.5)),
            "ssm_D": _w((lambda *s: torch.randn(*s, dtype=torch.bfloat16) * 0.2)(D)),
        }
    _A_in = _A_setup()

    def _B_setup():
        B, S, D, Dff = 1, 2048, 640, 1536
        return {
            "x": _w((lambda *s: torch.randn(*s, dtype=torch.bfloat16) * 0.05)(B, S, D)),
            "w1": _w((lambda *s: torch.randn(*s, dtype=torch.bfloat16) * 0.1)(D, Dff)),
            "w2": _w((lambda *s: torch.randn(*s, dtype=torch.bfloat16) * 0.1)(Dff, D)),
        }
    _B_in = _B_setup()

    return {
        "A_q": _A_in["q"],
        "A_k": _A_in["k"],
        "A_v": _A_in["v"],
        "A_shift_k": _A_in["shift_k"],
        "A_ssm_k": _A_in["ssm_k"],
        "A_ssm_D": _A_in["ssm_D"],
        "B_x": _B_in["x"],
        "B_w1": _B_in["w1"],
        "B_w2": _B_in["w2"],
    }

def reference(A_q, A_k, A_v, A_shift_k, A_ssm_k, A_ssm_D, B_x, B_w1, B_w2):
    def _A_ref(q, k, v, shift_k, ssm_k, ssm_D):
        B, S, D = q.shape
        ks = shift_k.shape[-1]
        k_pad = _pad(k, ((0, 0), (ks - 1, 0), (0, 0)))
        k_shift = torch.zeros_like(k)
        for t in range(ks):
            k_shift = k_shift + k_pad[:, t:t + S, :] * shift_k[:, ks - 1 - t][None, None, :]
        kv = k_shift * v
        L = 2 * S
        kv_pad = _pad(kv, ((0, 0), (0, S), (0, 0)))
        kf_pad = _pad(ssm_k, ((0, 0), (0, S)))
        kv_f = (lambda x, axes=(-2,-1): torch.fft.rfft2(x.float(), dim=axes))(kv_pad[:, None, :, :], axes=(1, 2))
        kf_f = (lambda x, axes=(-2,-1): torch.fft.rfft2(x.float(), dim=axes))(kf_pad[:, None, :], axes=(1, 2))
        kf_f = (lambda x, *d: x.permute(*d))(kf_f, 1, 2, 0)
        y_f = kv_f * kf_f[None, :, :, :]
        y = (lambda x, s, axes=(-2,-1): torch.fft.irfft2(x, s=s, dim=axes).to(torch.bfloat16))(y_f, (1, L), axes=(1, 2))[:, 0, :S, :]
        y = y + kv * ssm_D[None, None, :]
        return q * y

    def _B_ref(x, w1, w2):
        h = torch.einsum("bsd,df->bsf", x, w1)
        zero = torch.zeros_like(h)
        h = torch.maximum(h, zero)
        return torch.einsum("bsf,fd->bsd", h, w2)

    x = A_q
    xn = _layernorm(x, axis=-1)
    s = _A_ref(xn, A_k, A_v, A_shift_k, A_ssm_k, A_ssm_D)
    g = _silu(_B_ref(xn, B_w1, B_w2))
    return x + s * g
```

```cpp
#include <cuda_runtime.h>
#include <cuda_bf16.h>
#include <cuda.h>
#include <stdint.h>

namespace mk {

constexpr int S_LEN = 2048, D_MODEL = 640, D_FF = 1536;
constexpr int NCTA = 128;
constexpr int NTHR = 384;
constexpr int CH_PER_CTA = 5;

__device__ __align__(1024) __nv_bfloat16 g_xn[S_LEN * D_MODEL];
__device__ __align__(1024) __nv_bfloat16 g_kvT[D_MODEL * S_LEN];
__device__ __align__(1024) __nv_bfloat16 g_w2T[D_MODEL * D_FF];
__device__ __align__(1024) __nv_bfloat16 g_h[S_LEN * D_FF];
__device__ __align__(1024) __nv_bfloat16 g_tT[D_MODEL * S_LEN];
constexpr int FL_XN = 0;
constexpr int FL_PREP = 16;
constexpr int FL_H = 17;
constexpr int FL_T = 33;
constexpr int FL_DONE = 41;
constexpr int FL_ERR = 42;
constexpr int NFLAGS = 43;
__device__ unsigned g_flags[NFLAGS * 32];

#define TSTAMP(i, cond) do {} while (0)
__device__ __forceinline__ uint32_t smem_u32(const void* p) { return (uint32_t)__cvta_generic_to_shared(p); }
__device__ __forceinline__ void mbar_init(uint32_t bar, uint32_t cnt) { asm volatile("mbarrier.init.shared::cta.b64 [%0], %1;" :: "r"(bar), "r"(cnt)); }
__device__ __forceinline__ void mbar_expect_tx(uint32_t bar, uint32_t bytes) { asm volatile("mbarrier.arrive.expect_tx.shared::cta.b64 _, [%0], %1;" :: "r"(bar), "r"(bytes) : "memory"); }
__device__ __forceinline__ void mbar_arrive(uint32_t bar) { asm volatile("mbarrier.arrive.shared::cta.b64 _, [%0];" :: "r"(bar) : "memory"); }
__device__ __forceinline__ void mbar_wait(uint32_t bar, uint32_t parity) {
    uint32_t ok; int it = 0;
    do {
        asm volatile("{\n.reg .pred p;\nmbarrier.try_wait.parity.shared::cta.b64 p, [%1], %2;\nselp.u32 %0, 1, 0, p;\n}\n" : "=r"(ok) : "r"(bar), "r"(parity) : "memory");
        if (++it > (1 << 22)) { g_flags[FL_ERR * 32] = 1; __trap(); }
    } while (!ok);
}
__device__ __forceinline__ void tma_load_2d(uint32_t dst, const CUtensorMap* map, int c0, int c1, uint32_t bar) {
    asm volatile("cp.async.bulk.tensor.2d.shared::cluster.global.mbarrier::complete_tx::bytes [%0], [%1, {%3, %4}], [%2];"
        :: "r"(dst), "l"(map), "r"(bar), "r"(c0), "r"(c1) : "memory");
}
__device__ __forceinline__ void tma_load_3d(uint32_t dst, const CUtensorMap* map, int c0, int c1, int c2, uint32_t bar) {
    asm volatile("cp.async.bulk.tensor.3d.shared::cluster.global.mbarrier::complete_tx::bytes [%0], [%1, {%3, %4, %5}], [%2];"
        :: "r"(dst), "l"(map), "r"(bar), "r"(c0), "r"(c1), "r"(c2) : "memory");
}
__device__ __forceinline__ void tma_store_2d(const CUtensorMap* map, uint32_t src, int c0, int c1) {
    asm volatile("cp.async.bulk.tensor.2d.global.shared::cta.bulk_group [%0, {%2, %3}], [%1];" :: "l"(map), "r"(src), "r"(c0), "r"(c1) : "memory");
}
__device__ __forceinline__ void bulk_commit() { asm volatile("cp.async.bulk.commit_group;" ::: "memory"); }
__device__ __forceinline__ void bulk_wait_all() { asm volatile("cp.async.bulk.wait_group 0;" ::: "memory"); }
__device__ __forceinline__ void fence_proxy_async() { asm volatile("fence.proxy.async;" ::: "memory"); }
__device__ __forceinline__ void fence_proxy_async_smem() { asm volatile("fence.proxy.async.shared::cta;" ::: "memory"); }
__device__ __forceinline__ void named_bar(int id, int n) { asm volatile("bar.sync %0, %1;" :: "r"(id), "r"(n) : "memory"); }
__device__ __forceinline__ void wgmma_fence() { asm volatile("wgmma.fence.sync.aligned;\n" ::: "memory"); }
__device__ __forceinline__ void wgmma_commit() { asm volatile("wgmma.commit_group.sync.aligned;\n" ::: "memory"); }
template<int N> __device__ __forceinline__ void wgmma_wait() { asm volatile("wgmma.wait_group.sync.aligned %0;\n" :: "n"(N) : "memory"); }
__device__ __forceinline__ unsigned ld_acquire(const unsigned* p) { unsigned v; asm volatile("ld.acquire.gpu.global.u32 %0, [%1];" : "=r"(v) : "l"(p) : "memory"); return v; }
__device__ __forceinline__ void wait_flag(int idx, unsigned target) {
    const unsigned* p = &g_flags[idx * 32];
    int it = 0;
    while (ld_acquire(p) < target) { if (++it > (1 << 22)) { g_flags[FL_ERR * 32] = 2; __trap(); } }
}
__device__ __forceinline__ void signal_flag(int idx) {
    __threadfence();
    atomicAdd(&g_flags[idx * 32], 1u);
}
__device__ __forceinline__ float bf2f(__nv_bfloat16 v) { return __bfloat162float(v); }
__device__ __forceinline__ float rbf(float x) { return __bfloat162float(__float2bfloat16_rn(x)); }
__device__ __forceinline__ uint32_t pack_bf2(float lo, float hi) { __nv_bfloat162 v = __floats2bfloat162_rn(lo, hi); return *reinterpret_cast<uint32_t*>(&v); }
__device__ __forceinline__ float bflo(uint32_t w) { return __uint_as_float(w << 16); }
__device__ __forceinline__ float bfhi(uint32_t w) { return __uint_as_float(w & 0xffff0000u); }

__device__ __forceinline__ uint64_t desc_sw128(uint32_t addr, uint32_t lbo_bytes, uint32_t sbo_bytes) {
    return ((uint64_t)((addr & 0x3FFFF) >> 4)) | ((uint64_t)(lbo_bytes >> 4) << 16) | ((uint64_t)(sbo_bytes >> 4) << 32) | ((uint64_t)1 << 62);
}
__device__ __forceinline__ uint64_t desc_nosw(uint32_t addr, uint32_t lbo_bytes, uint32_t sbo_bytes) {
    return ((uint64_t)((addr & 0x3FFFF) >> 4)) | ((uint64_t)(lbo_bytes >> 4) << 16) | ((uint64_t)(sbo_bytes >> 4) << 32);
}

__device__ __forceinline__ void wgmma_rs_n8(float* d, uint32_t a0, uint32_t a1, uint32_t a2, uint32_t a3, uint64_t descB) {
    asm volatile("wgmma.mma_async.sync.aligned.m64n8k16.f32.bf16.bf16 {%0,%1,%2,%3}, {%4,%5,%6,%7}, %8, 1, 1, 1, 0;\n"
        : "+f"(d[0]), "+f"(d[1]), "+f"(d[2]), "+f"(d[3])
        : "r"(a0), "r"(a1), "r"(a2), "r"(a3), "l"(descB));
}
__device__ __forceinline__ void wgmma_rs_n16(float* d, uint32_t a0, uint32_t a1, uint32_t a2, uint32_t a3, uint64_t descB) {
    asm volatile("wgmma.mma_async.sync.aligned.m64n16k16.f32.bf16.bf16 {%0,%1,%2,%3,%4,%5,%6,%7}, {%8,%9,%10,%11}, %12, 1, 1, 1, 0;\n"
        : "+f"(d[0]), "+f"(d[1]), "+f"(d[2]), "+f"(d[3]), "+f"(d[4]), "+f"(d[5]), "+f"(d[6]), "+f"(d[7])
        : "r"(a0), "r"(a1), "r"(a2), "r"(a3), "l"(descB));
}
__device__ __forceinline__ void wgmma_rs_n24(float* d, uint32_t a0, uint32_t a1, uint32_t a2, uint32_t a3, uint64_t descB) {
    asm volatile("wgmma.mma_async.sync.aligned.m64n24k16.f32.bf16.bf16 {%0,%1,%2,%3,%4,%5,%6,%7,%8,%9,%10,%11}, {%12,%13,%14,%15}, %16, 1, 1, 1, 0;\n"
        : "+f"(d[0]), "+f"(d[1]), "+f"(d[2]), "+f"(d[3]), "+f"(d[4]), "+f"(d[5]), "+f"(d[6]), "+f"(d[7]), "+f"(d[8]), "+f"(d[9]), "+f"(d[10]), "+f"(d[11])
        : "r"(a0), "r"(a1), "r"(a2), "r"(a3), "l"(descB));
}
__device__ __forceinline__ void wgmma_rs_n32(float* d, uint32_t a0, uint32_t a1, uint32_t a2, uint32_t a3, uint64_t descB) {
    asm volatile("wgmma.mma_async.sync.aligned.m64n32k16.f32.bf16.bf16 {%0,%1,%2,%3,%4,%5,%6,%7,%8,%9,%10,%11,%12,%13,%14,%15}, {%16,%17,%18,%19}, %20, 1, 1, 1, 0;\n"
        : "+f"(d[0]), "+f"(d[1]), "+f"(d[2]), "+f"(d[3]), "+f"(d[4]), "+f"(d[5]), "+f"(d[6]), "+f"(d[7]), "+f"(d[8]), "+f"(d[9]), "+f"(d[10]), "+f"(d[11]), "+f"(d[12]), "+f"(d[13]), "+f"(d[14]), "+f"(d[15])
        : "r"(a0), "r"(a1), "r"(a2), "r"(a3), "l"(descB));
}
__device__ __forceinline__ void wgmma_ss_n192(float* d, uint64_t descA, uint64_t descB) {
    asm volatile("wgmma.mma_async.sync.aligned.m64n192k16.f32.bf16.bf16 {%0,%1,%2,%3,%4,%5,%6,%7,%8,%9,%10,%11,%12,%13,%14,%15,%16,%17,%18,%19,%20,%21,%22,%23,%24,%25,%26,%27,%28,%29,%30,%31,%32,%33,%34,%35,%36,%37,%38,%39,%40,%41,%42,%43,%44,%45,%46,%47,%48,%49,%50,%51,%52,%53,%54,%55,%56,%57,%58,%59,%60,%61,%62,%63,%64,%65,%66,%67,%68,%69,%70,%71,%72,%73,%74,%75,%76,%77,%78,%79,%80,%81,%82,%83,%84,%85,%86,%87,%88,%89,%90,%91,%92,%93,%94,%95}, %96, %97, 1, 1, 1, 0, 1;\n"
        : "+f"(d[0]), "+f"(d[1]), "+f"(d[2]), "+f"(d[3]), "+f"(d[4]), "+f"(d[5]), "+f"(d[6]), "+f"(d[7]), "+f"(d[8]), "+f"(d[9]), "+f"(d[10]), "+f"(d[11]), "+f"(d[12]), "+f"(d[13]), "+f"(d[14]), "+f"(d[15]), "+f"(d[16]), "+f"(d[17]), "+f"(d[18]), "+f"(d[19]), "+f"(d[20]), "+f"(d[21]), "+f"(d[22]), "+f"(d[23]), "+f"(d[24]), "+f"(d[25]), "+f"(d[26]), "+f"(d[27]), "+f"(d[28]), "+f"(d[29]), "+f"(d[30]), "+f"(d[31]), "+f"(d[32]), "+f"(d[33]), "+f"(d[34]), "+f"(d[35]), "+f"(d[36]), "+f"(d[37]), "+f"(d[38]), "+f"(d[39]), "+f"(d[40]), "+f"(d[41]), "+f"(d[42]), "+f"(d[43]), "+f"(d[44]), "+f"(d[45]), "+f"(d[46]), "+f"(d[47]), "+f"(d[48]), "+f"(d[49]), "+f"(d[50]), "+f"(d[51]), "+f"(d[52]), "+f"(d[53]), "+f"(d[54]), "+f"(d[55]), "+f"(d[56]), "+f"(d[57]), "+f"(d[58]), "+f"(d[59]), "+f"(d[60]), "+f"(d[61]), "+f"(d[62]), "+f"(d[63]), "+f"(d[64]), "+f"(d[65]), "+f"(d[66]), "+f"(d[67]), "+f"(d[68]), "+f"(d[69]), "+f"(d[70]), "+f"(d[71]), "+f"(d[72]), "+f"(d[73]), "+f"(d[74]), "+f"(d[75]), "+f"(d[76]), "+f"(d[77]), "+f"(d[78]), "+f"(d[79]), "+f"(d[80]), "+f"(d[81]), "+f"(d[82]), "+f"(d[83]), "+f"(d[84]), "+f"(d[85]), "+f"(d[86]), "+f"(d[87]), "+f"(d[88]), "+f"(d[89]), "+f"(d[90]), "+f"(d[91]), "+f"(d[92]), "+f"(d[93]), "+f"(d[94]), "+f"(d[95])
        : "l"(descA), "l"(descB));
}
__device__ __forceinline__ void wgmma_ss_n80(float* d, uint64_t descA, uint64_t descB) {
    asm volatile("wgmma.mma_async.sync.aligned.m64n80k16.f32.bf16.bf16 {%0,%1,%2,%3,%4,%5,%6,%7,%8,%9,%10,%11,%12,%13,%14,%15,%16,%17,%18,%19,%20,%21,%22,%23,%24,%25,%26,%27,%28,%29,%30,%31,%32,%33,%34,%35,%36,%37,%38,%39}, %40, %41, 1, 1, 1, 0, 0;\n"
        : "+f"(d[0]), "+f"(d[1]), "+f"(d[2]), "+f"(d[3]), "+f"(d[4]), "+f"(d[5]), "+f"(d[6]), "+f"(d[7]), "+f"(d[8]), "+f"(d[9]), "+f"(d[10]), "+f"(d[11]), "+f"(d[12]), "+f"(d[13]), "+f"(d[14]), "+f"(d[15]), "+f"(d[16]), "+f"(d[17]), "+f"(d[18]), "+f"(d[19]), "+f"(d[20]), "+f"(d[21]), "+f"(d[22]), "+f"(d[23]), "+f"(d[24]), "+f"(d[25]), "+f"(d[26]), "+f"(d[27]), "+f"(d[28]), "+f"(d[29]), "+f"(d[30]), "+f"(d[31]), "+f"(d[32]), "+f"(d[33]), "+f"(d[34]), "+f"(d[35]), "+f"(d[36]), "+f"(d[37]), "+f"(d[38]), "+f"(d[39])
        : "l"(descA), "l"(descB));
}

constexpr int SM_PIPE = 0;
constexpr int ST1_BYTES = 40960, ST1_N = 4;
constexpr int ST2_BYTES = 53248, ST2_N = 3;
constexpr int U_STRIP = 656;
constexpr int U_BYTES = 8 * U_STRIP;
constexpr int SM_U = 163840;
constexpr int F_COPY1 = 4224 + 64;
constexpr int F_BYTES = F_COPY1 + 4224;
constexpr int SM_F = SM_U + 2 * U_BYTES;
constexpr int SM_X = SM_F + 2 * F_BYTES;
constexpr int SM_T = SM_X + 8192;
constexpr int SM_BAR = SM_T + 4096;
constexpr int SM_TOTAL = SM_BAR + 256;
constexpr int B_FULL1 = 0, B_EMPTY1 = 4, B_FULL2 = 8, B_EMPTY2 = 11, B_G1DONE = 14;

struct Params {
    CUtensorMap tm_xn, tm_w1, tm_hst, tm_h, tm_w2T, tm_xn_e, tm_q_e, tm_tT_e;
    const __nv_bfloat16 *q, *k, *v, *shift_k, *ssm_k, *ssm_D, *w2;
    __nv_bfloat16* out;
};

__device__ __forceinline__ void prep_phase(const Params& p, uint8_t* smem, int cta) {
    const int tid = threadIdx.x, warp = tid >> 5, lane = tid & 31;
    const int s0 = cta * 16;
    if (warp < 8) {
        #pragma unroll
        for (int rr = 0; rr < 2; rr++) {
            const int row = s0 + warp * 2 + rr;
            const __nv_bfloat16* xr = p.q + (size_t)row * D_MODEL;
            uint4 a = *reinterpret_cast<const uint4*>(xr + lane * 8);
            uint4 b = *reinterpret_cast<const uint4*>(xr + 256 + lane * 8);
            uint2 c = *reinterpret_cast<const uint2*>(xr + 512 + lane * 4);
            uint32_t w[10] = {a.x, a.y, a.z, a.w, b.x, b.y, b.z, b.w, c.x, c.y};
            float x[20];
            #pragma unroll
            for (int i = 0; i < 10; i++) { x[2 * i] = bflo(w[i]); x[2 * i + 1] = bfhi(w[i]); }
            float sum = 0.f;
            #pragma unroll
            for (int i = 0; i < 20; i++) sum += x[i];
            #pragma unroll
            for (int o = 16; o > 0; o >>= 1) sum += __shfl_xor_sync(0xffffffffu, sum, o);
            const float mean = sum * (1.0f / 640.0f);
            float sq = 0.f;
            #pragma unroll
            for (int i = 0; i < 20; i++) { float d = x[i] - mean; sq += d * d; }
            #pragma unroll
            for (int o = 16; o > 0; o >>= 1) sq += __shfl_xor_sync(0xffffffffu, sq, o);
            const float var_b = rbf(sq * (1.0f / 640.0f));
            const float m_b = rbf(mean);
            const float den = rbf(__fsqrt_rn(rbf(var_b + 1e-5f)));
            uint32_t o[10];
            #pragma unroll
            for (int i = 0; i < 10; i++) {
                float y0 = __fdiv_rn(rbf(x[2 * i] - m_b), den);
                float y1 = __fdiv_rn(rbf(x[2 * i + 1] - m_b), den);
                o[i] = pack_bf2(y0, y1);
            }
            __nv_bfloat16* yr = g_xn + (size_t)row * D_MODEL;
            *reinterpret_cast<uint4*>(yr + lane * 8) = make_uint4(o[0], o[1], o[2], o[3]);
            *reinterpret_cast<uint4*>(yr + 256 + lane * 8) = make_uint4(o[4], o[5], o[6], o[7]);
            *reinterpret_cast<uint2*>(yr + 512 + lane * 4) = make_uint2(o[8], o[9]);
        }
    } else {
        const int t = tid - 256;
        const int k0 = (cta >> 3) * 96, n0 = (cta & 7) * 80;
        uint8_t* stg = smem + SM_U;
        for (int idx = t; idx < 960; idx += 128) {
            const int r = idx / 10, c = idx % 10;
            uint4 v4 = *reinterpret_cast<const uint4*>(p.w2 + (size_t)(k0 + r) * D_MODEL + n0 + c * 8);
            uint32_t w[4] = {v4.x, v4.y, v4.z, v4.w};
            #pragma unroll
            for (int e = 0; e < 4; e++) {
                *reinterpret_cast<uint16_t*>(stg + (c * 8 + 2 * e) * 208 + r * 2) = (uint16_t)(w[e] & 0xffffu);
                *reinterpret_cast<uint16_t*>(stg + (c * 8 + 2 * e + 1) * 208 + r * 2) = (uint16_t)(w[e] >> 16);
            }
        }
        named_bar(3, 128);
        for (int idx = t; idx < 960; idx += 128) {
            const int n = idx / 12, c = idx % 12;
            uint4 v4 = *reinterpret_cast<const uint4*>(stg + n * 208 + c * 16);
            *reinterpret_cast<uint4*>(g_w2T + (size_t)(n0 + n) * D_FF + k0 + c * 8) = v4;
        }
    }
    if (tid < 320) {
        const int d = tid * 2;
        uint4 sk = *reinterpret_cast<const uint4*>(p.shift_k + d * 4);
        const float w00 = bflo(sk.x), w01 = bfhi(sk.x), w02 = bflo(sk.y), w03 = bfhi(sk.y);
        const float w10 = bflo(sk.z), w11 = bfhi(sk.z), w12 = bflo(sk.w), w13 = bfhi(sk.w);
        uint32_t kw[19], vw[16];
        #pragma unroll
        for (int j = 0; j < 19; j++) {
            const int row = s0 - 3 + j;
            kw[j] = (row >= 0) ? *reinterpret_cast<const uint32_t*>(p.k + (size_t)row * D_MODEL + d) : 0u;
        }
        #pragma unroll
        for (int j = 0; j < 16; j++) vw[j] = *reinterpret_cast<const uint32_t*>(p.v + (size_t)(s0 + j) * D_MODEL + d);
        uint32_t o0[8], o1[8];
        float r0[16], r1[16];
        #pragma unroll
        for (int j = 0; j < 16; j++) {
            float a = rbf(bflo(kw[j]) * w03);
            a = rbf(a + rbf(bflo(kw[j + 1]) * w02));
            a = rbf(a + rbf(bflo(kw[j + 2]) * w01));
            a = rbf(a + rbf(bflo(kw[j + 3]) * w00));
            r0[j] = a * bflo(vw[j]);
            float b = rbf(bfhi(kw[j]) * w13);
            b = rbf(b + rbf(bfhi(kw[j + 1]) * w12));
            b = rbf(b + rbf(bfhi(kw[j + 2]) * w11));
            b = rbf(b + rbf(bfhi(kw[j + 3]) * w10));
            r1[j] = b * bfhi(vw[j]);
        }
        #pragma unroll
        for (int j = 0; j < 8; j++) { o0[j] = pack_bf2(r0[2 * j], r0[2 * j + 1]); o1[j] = pack_bf2(r1[2 * j], r1[2 * j + 1]); }
        uint4* d0 = reinterpret_cast<uint4*>(g_kvT + (size_t)d * S_LEN + s0);
        uint4* d1 = reinterpret_cast<uint4*>(g_kvT + (size_t)(d + 1) * S_LEN + s0);
        d0[0] = make_uint4(o0[0], o0[1], o0[2], o0[3]); d0[1] = make_uint4(o0[4], o0[5], o0[6], o0[7]);
        d1[0] = make_uint4(o1[0], o1[1], o1[2], o1[3]); d1[1] = make_uint4(o1[4], o1[5], o1[6], o1[7]);
    }
}

__device__ __forceinline__ void stmatrix_x4(uint32_t addr, uint32_t r0, uint32_t r1, uint32_t r2, uint32_t r3) {
    asm volatile("stmatrix.sync.aligned.m8n8.x4.shared.b16 [%0], {%1, %2, %3, %4};" :: "r"(addr), "r"(r0), "r"(r1), "r"(r2), "r"(r3) : "memory");
}
__device__ __forceinline__ uint32_t lds32(uint32_t addr) { uint32_t v; asm volatile("ld.shared.u32 %0, [%1];" : "=r"(v) : "r"(addr)); return v; }

template<int E>
__device__ __forceinline__ void conv_mma4(float* acc, const uint32_t (&A)[16], uint64_t descB) {
    #pragma unroll
    for (int kk = 0; kk < 4; kk++) {
        const uint64_t db = descB + (uint64_t)((2 * kk * U_STRIP) >> 4);
        if (E == 0) wgmma_rs_n32(acc, A[4 * kk], A[4 * kk + 1], A[4 * kk + 2], A[4 * kk + 3], db);
        if (E == 1) wgmma_rs_n24(acc, A[4 * kk], A[4 * kk + 1], A[4 * kk + 2], A[4 * kk + 3], db);
        if (E == 2) wgmma_rs_n16(acc, A[4 * kk], A[4 * kk + 1], A[4 * kk + 2], A[4 * kk + 3], db);
        if (E == 3) wgmma_rs_n8(acc, A[4 * kk], A[4 * kk + 1], A[4 * kk + 2], A[4 * kk + 3], db);
    }
}
__device__ __forceinline__ uint32_t swap16(uint32_t x) { uint32_t r; asm volatile("prmt.b32 %0, %1, 0, 0x1032;" : "=r"(r) : "r"(x)); return r; }
__device__ __forceinline__ void conv_loadP(uint32_t (&A)[16], uint32_t pfa, int c) {
    uint32_t P[9];
    #pragma unroll
    for (int j = 0; j < 9; j++) P[j] = lds32(pfa + c * 128 + j * 16);
    #pragma unroll
    for (int kk = 0; kk < 4; kk++) {
        A[4 * kk + 0] = swap16(P[7 - 2 * kk]);
        A[4 * kk + 1] = swap16(P[8 - 2 * kk]);
        A[4 * kk + 2] = swap16(P[6 - 2 * kk]);
        A[4 * kk + 3] = swap16(P[7 - 2 * kk]);
    }
}

__global__ void __launch_bounds__(NTHR, 1) mega_kernel(const __grid_constant__ Params p) {
    extern __shared__ __align__(1024) uint8_t smem[];
    const int tid = threadIdx.x, warp = tid >> 5, lane = tid & 31;
    const int cta = blockIdx.x;
    const int tb = cta >> 3, ns = cta & 7;
    const uint32_t sbase = smem_u32(smem);
    const uint32_t bar0 = sbase + SM_BAR;
    #define BAR(i) (bar0 + (i) * 8)

    if (tid == 0) {
        for (int i = 0; i < ST1_N; i++) { mbar_init(BAR(B_FULL1 + i), 1); mbar_init(BAR(B_EMPTY1 + i), 2); }
        for (int i = 0; i < ST2_N; i++) { mbar_init(BAR(B_FULL2 + i), 1); mbar_init(BAR(B_EMPTY2 + i), 2); }
        mbar_init(BAR(B_G1DONE), 2);
        asm volatile("fence.mbarrier_init.release.cluster;" ::: "memory");
    }
    prep_phase(p, smem, cta);
    __syncthreads();
    if (tid == 0) { __threadfence(); atomicAdd(&g_flags[(FL_XN + tb) * 32], 1u); atomicAdd(&g_flags[FL_PREP * 32], 1u); }
    TSTAMP(0, tid == 0);

    if (warp >= 8) {
        if (warp == 8 && lane == 0) {
            wait_flag(FL_XN + tb, 8);
            fence_proxy_async();
            for (int kb = 0; kb < 10; kb++) {
                const int s = kb % ST1_N;
                if (kb >= ST1_N) mbar_wait(BAR(B_EMPTY1 + s), ((kb / ST1_N) - 1) & 1);
                const uint32_t st = sbase + SM_PIPE + s * ST1_BYTES;
                mbar_expect_tx(BAR(B_FULL1 + s), ST1_BYTES);
                tma_load_2d(st, &p.tm_xn, kb * 64, tb * 128, BAR(B_FULL1 + s));
                tma_load_3d(st + 16384, &p.tm_w1, 0, kb * 64, ns * 3, BAR(B_FULL1 + s));
            }
            mbar_wait(BAR(B_G1DONE), 0);
            wait_flag(FL_PREP, NCTA);
            wait_flag(FL_H + tb, 16);
            fence_proxy_async();
            for (int it = 0; it < 12; it++) {
                const int s = it % ST2_N;
                if (it >= ST2_N) mbar_wait(BAR(B_EMPTY2 + s), ((it / ST2_N) - 1) & 1);
                const uint32_t st = sbase + SM_PIPE + s * ST2_BYTES;
                mbar_expect_tx(BAR(B_FULL2 + s), ST2_BYTES);
                tma_load_3d(st, &p.tm_h, 0, tb * 128, it * 2, BAR(B_FULL2 + s));
                tma_load_3d(st + 32768, &p.tm_w2T, 0, ns * 80, it * 2, BAR(B_FULL2 + s));
            }
            mbar_wait(BAR(B_EMPTY2 + 0), ((12 / ST2_N) - 1) & 1);
            mbar_expect_tx(BAR(B_FULL2 + 0), 2 * 20480);
            tma_load_2d(sbase + SM_PIPE, &p.tm_xn_e, ns * 80, tb * 128, BAR(B_FULL2 + 0));
            tma_load_2d(sbase + SM_PIPE + 20480, &p.tm_q_e, ns * 80, tb * 128, BAR(B_FULL2 + 0));
            mbar_wait(BAR(B_EMPTY2 + 1), ((13 / ST2_N) - 1) & 1);
            wait_flag(FL_T + ns, 16);
            fence_proxy_async();
            mbar_expect_tx(BAR(B_FULL2 + 1), 20480);
            tma_load_2d(sbase + SM_PIPE + ST2_BYTES, &p.tm_tT_e, tb * 128, ns * 80, BAR(B_FULL2 + 1));
        }
    } else {
        const int wg = warp >> 2;
        const int w = warp & 3;
        const int wt = tid & 127;
        const int g = lane >> 2, q = lane & 3;
        {
            float acc[96];
            #pragma unroll
            for (int i = 0; i < 96; i++) acc[i] = 0.f;
            for (int kb = 0; kb < 10; kb++) {
                const int s = kb % ST1_N;
                mbar_wait(BAR(B_FULL1 + s), (kb / ST1_N) & 1);
                const uint32_t sa = sbase + SM_PIPE + s * ST1_BYTES + wg * 8192;
                const uint32_t sb = sbase + SM_PIPE + s * ST1_BYTES + 16384;
                wgmma_fence();
                #pragma unroll
                for (int kk = 0; kk < 4; kk++)
                    wgmma_ss_n192(acc, desc_sw128(sa + kk * 32, 16, 1024), desc_sw128(sb + kk * 2048, 8192, 1024));
                wgmma_commit();
                wgmma_wait<0>();
                if (wt == 0) mbar_arrive(BAR(B_EMPTY1 + s));
            }
            TSTAMP(1, tid == 0);
            named_bar(1, 256);
            const uint32_t stg = sbase + SM_PIPE;
            const int m = lane >> 3, r = lane & 7;
            const int row = 16 * w + (m & 1) * 8 + r;
            #pragma unroll
            for (int j2 = 0; j2 < 12; j2++) {
                const int nb = j2 >> 2, cb = (2 * j2) & 7;
                uint32_t r0 = pack_bf2(fmaxf(acc[8 * j2 + 0], 0.f), fmaxf(acc[8 * j2 + 1], 0.f));
                uint32_t r1 = pack_bf2(fmaxf(acc[8 * j2 + 2], 0.f), fmaxf(acc[8 * j2 + 3], 0.f));
                uint32_t r2 = pack_bf2(fmaxf(acc[8 * j2 + 4], 0.f), fmaxf(acc[8 * j2 + 5], 0.f));
                uint32_t r3 = pack_bf2(fmaxf(acc[8 * j2 + 6], 0.f), fmaxf(acc[8 * j2 + 7], 0.f));
                const int chunk = cb + (m >> 1);
                stmatrix_x4(stg + nb * 16384 + wg * 8192 + row * 128 + ((chunk ^ (row & 7)) << 4), r0, r1, r2, r3);
            }
            fence_proxy_async_smem();
            named_bar(2 + wg, 128);
            if (wt == 0) {
                #pragma unroll
                for (int nb = 0; nb < 3; nb++)
                    tma_store_2d(&p.tm_hst, stg + nb * 16384 + wg * 8192, ns * 192 + nb * 64, tb * 128 + wg * 64);
                bulk_commit();
                bulk_wait_all();
                mbar_arrive(BAR(B_G1DONE));
                signal_flag(FL_H + tb);
            }
        }
        TSTAMP(2, tid == 0);
        {
            for (int i = tid; i < 2 * 8 * 8; i += 256) {
                const int bufi = i >> 6, st = (i >> 3) & 7, rr = i & 7;
                *reinterpret_cast<uint4*>(smem + SM_U + bufi * U_BYTES + st * U_STRIP + rr * 16) = make_uint4(0, 0, 0, 0);
            }
            if (tid < 32) {
                const int bufi = tid >> 4, cp = (tid >> 3) & 1, rr = tid & 7;
                *reinterpret_cast<uint4*>(smem + SM_F + bufi * F_BYTES + cp * F_COPY1 + rr * 16) = make_uint4(0, 0, 0, 0);
            }
            if (tid == 0) wait_flag(FL_PREP, NCTA);
            named_bar(1, 256);
            TSTAMP(3, tid == 0);
            const int d0 = cta * CH_PER_CTA;
            uint4 pu = *reinterpret_cast<const uint4*>(g_kvT + (size_t)d0 * S_LEN + tid * 8);
            uint4 pf = *reinterpret_cast<const uint4*>(p.ssm_k + (size_t)d0 * S_LEN + tid * 8);
            uint32_t pprev = (tid > 0) ? (uint32_t)*reinterpret_cast<const uint16_t*>(p.ssm_k + (size_t)d0 * S_LEN + tid * 8 - 1) : 0u;
            const uint32_t pf_off = (g & 1) ? (128 + 2 * (g - 1 - 2 * q)) : (F_COPY1 + 128 + 2 * (g - 2 * q));
            for (int ch = 0; ch < CH_PER_CTA; ch++) {
                const int buf = ch & 1;
                const int d = d0 + ch;
                uint8_t* ub = smem + SM_U + buf * U_BYTES;
                uint8_t* fb = smem + SM_F + buf * F_BYTES;
                *reinterpret_cast<uint4*>(ub + (tid & 7) * U_STRIP + ((tid >> 3) + 8) * 16) = pu;
                *reinterpret_cast<uint4*>(fb + 128 + tid * 16) = pf;
                *reinterpret_cast<uint4*>(fb + F_COPY1 + 128 + tid * 16) =
                    make_uint4(__byte_perm(pprev, pf.x, 0x5410), __byte_perm(pf.x, pf.y, 0x5432), __byte_perm(pf.y, pf.z, 0x5432), __byte_perm(pf.z, pf.w, 0x5432));
                fence_proxy_async_smem();
                named_bar(1, 256);
                if (ch + 1 < CH_PER_CTA) {
                    pu = *reinterpret_cast<const uint4*>(g_kvT + (size_t)(d + 1) * S_LEN + tid * 8);
                    pf = *reinterpret_cast<const uint4*>(p.ssm_k + (size_t)(d + 1) * S_LEN + tid * 8);
                    pprev = (tid > 0) ? (uint32_t)*reinterpret_cast<const uint16_t*>(p.ssm_k + (size_t)(d + 1) * S_LEN + tid * 8 - 1) : 0u;
                }
                TSTAMP(8 + (ch < 2 ? ch * 3 : 6), tid == 0);
                float acc0[16], acc1[12], acc2[8], acc3[4];
                #pragma unroll
                for (int i = 0; i < 16; i++) acc0[i] = 0.f;
                #pragma unroll
                for (int i = 0; i < 12; i++) acc1[i] = 0.f;
                #pragma unroll
                for (int i = 0; i < 8; i++) acc2[i] = 0.f;
                #pragma unroll
                for (int i = 0; i < 4; i++) acc3[i] = 0.f;
                const uint32_t pfa = smem_u32(fb) + pf_off + 32 * w - 7 * 16;
                const uint32_t ubs = smem_u32(ub);
                uint32_t A0[16], A1[16];
                conv_loadP(A0, pfa, wg);
                #define CONV_GROUP(E, ACC) \
                    { \
                        _Pragma("unroll") \
                        for (int r = 0; r < 4; r += 2) { \
                            int c = 8 * E + 2 * r + wg; \
                            wgmma_fence(); \
                            conv_mma4<E>(ACC, A0, desc_nosw(ubs + (8 * E - c + 8) * 16, U_STRIP, 128)); \
                            wgmma_commit(); \
                            wgmma_wait<1>(); \
                            conv_loadP(A1, pfa, c + 2); \
                            c += 2; \
                            wgmma_fence(); \
                            conv_mma4<E>(ACC, A1, desc_nosw(ubs + (8 * E - c + 8) * 16, U_STRIP, 128)); \
                            wgmma_commit(); \
                            if (E == 3 && r == 2) { wgmma_wait<0>(); } \
                            else { wgmma_wait<1>(); conv_loadP(A0, pfa, c + 2); } \
                        } \
                    }
                CONV_GROUP(0, acc0) CONV_GROUP(1, acc1) CONV_GROUP(2, acc2) CONV_GROUP(3, acc3)
                float acc[16];
                #pragma unroll
                for (int i = 0; i < 16; i++) {
                    float v = acc0[i];
                    if (i >= 4) v += acc1[i - 4];
                    if (i >= 8) v += acc2[i - 8];
                    if (i >= 12) v += acc3[i - 12];
                    acc[i] = v;
                }
                TSTAMP(9 + (ch < 2 ? ch * 3 : 6), tid == 0);
                float* X = reinterpret_cast<float*>(smem + SM_X);
                #pragma unroll
                for (int i = 0; i < 8; i++) X[(wg * 8 + i) * 128 + wt] = wg == 0 ? acc[8 + i] : acc[i];
                named_bar(1, 256);
                const float Dd = bf2f(p.ssm_D[d]);
                __nv_bfloat16* T = reinterpret_cast<__nv_bfloat16*>(smem + SM_T);
                #pragma unroll
                for (int i = 0; i < 8; i++) {
                    const float y = (wg == 0 ? acc[i] : acc[8 + i]) + X[((1 - wg) * 8 + i) * 128 + wt];
                    const int j = 2 * wg + (i >> 2);
                    const int a = 8 * j + 2 * q + (i & 1);
                    const int b = 16 * w + g + ((i >> 1) & 1) * 8;
                    const float u = bf2f(*reinterpret_cast<const __nv_bfloat16*>(ub + (b >> 3) * U_STRIP + (a + 8) * 16 + (b & 7) * 2));
                    T[64 * a + b] = __float2bfloat16_rn(rbf(y) + rbf(u * Dd));
                }
                named_bar(1, 256);
                *reinterpret_cast<uint4*>(g_tT + (size_t)d * S_LEN + tid * 8) = *reinterpret_cast<const uint4*>(smem + SM_T + tid * 16);
                TSTAMP(10 + (ch < 2 ? ch * 3 : 6), tid == 0);
            }
            named_bar(1, 256);
            if (tid == 0) signal_flag(FL_T + (cta >> 4));
        }
        TSTAMP(4, tid == 0);
        {
            float acc[40];
            #pragma unroll
            for (int i = 0; i < 40; i++) acc[i] = 0.f;
            for (int it = 0; it < 12; it++) {
                const int s = it % ST2_N;
                mbar_wait(BAR(B_FULL2 + s), (it / ST2_N) & 1);
                const uint32_t st = sbase + SM_PIPE + s * ST2_BYTES;
                wgmma_fence();
                #pragma unroll
                for (int kb2 = 0; kb2 < 2; kb2++)
                    #pragma unroll
                    for (int kk = 0; kk < 4; kk++)
                        wgmma_ss_n80(acc, desc_sw128(st + kb2 * 16384 + wg * 8192 + kk * 32, 16, 1024), desc_sw128(st + 32768 + kb2 * 10240 + kk * 32, 16, 1024));
                wgmma_commit();
                wgmma_wait<0>();
                if (wt == 0) mbar_arrive(BAR(B_EMPTY2 + s));
            }
            TSTAMP(5, tid == 0);
            mbar_wait(BAR(B_FULL2 + 0), (12 / ST2_N) & 1);
            mbar_wait(BAR(B_FULL2 + 1), (13 / ST2_N) & 1);
            TSTAMP(6, tid == 0);
            const uint8_t* xn_t = smem + SM_PIPE;
            const uint8_t* q_t = smem + SM_PIPE + 20480;
            const uint8_t* tT_t = smem + SM_PIPE + ST2_BYTES;
            #pragma unroll
            for (int j = 0; j < 10; j++) {
                #pragma unroll
                for (int hh = 0; hh < 2; hh++) {
                    const int row = 64 * wg + 16 * w + g + 8 * hh;
                    const int col = 8 * j + 2 * q;
                    const uint32_t xnw = *reinterpret_cast<const uint32_t*>(xn_t + row * 160 + col * 2);
                    const uint32_t qw = *reinterpret_cast<const uint32_t*>(q_t + row * 160 + col * 2);
                    const float t0 = bf2f(*reinterpret_cast<const __nv_bfloat16*>(tT_t + col * 256 + row * 2));
                    const float t1 = bf2f(*reinterpret_cast<const __nv_bfloat16*>(tT_t + (col + 1) * 256 + row * 2));
                    const float o0 = rbf(acc[4 * j + 2 * hh]), o1 = rbf(acc[4 * j + 2 * hh + 1]);
                    const float g0 = rbf(__fdividef(o0, 1.0f + __expf(-o0))), g1 = rbf(__fdividef(o1, 1.0f + __expf(-o1)));
                    const float s0 = rbf(bflo(xnw) * t0), s1 = rbf(bfhi(xnw) * t1);
                    const float r0 = bflo(qw) + rbf(s0 * g0), r1 = bfhi(qw) + rbf(s1 * g1);
                    *reinterpret_cast<uint32_t*>(p.out + (size_t)(tb * 128 + row) * D_MODEL + ns * 80 + col) = pack_bf2(r0, r1);
                }
            }
        }
    }
    __syncthreads();
    TSTAMP(7, tid == 0);
    if (tid == 0) {
        __threadfence();
        const unsigned dn = atomicAdd(&g_flags[FL_DONE * 32], 1u);
        if (dn == NCTA - 1) {
            for (int i = 0; i < NFLAGS; i++) g_flags[i * 32] = 0;
            __threadfence();
        }
    }
}

typedef CUresult (*PFN_encodeTiled)(CUtensorMap*, CUtensorMapDataType, cuuint32_t, void*, const cuuint64_t*, const cuuint64_t*, const cuuint32_t*, const cuuint32_t*,
                                    CUtensorMapInterleave, CUtensorMapSwizzle, CUtensorMapL2promotion, CUtensorMapFloatOOBfill);
static PFN_encodeTiled get_encode() {
    static PFN_encodeTiled fn = nullptr;
    if (!fn) {
        void* f = nullptr; cudaDriverEntryPointQueryResult qr;
        cudaGetDriverEntryPoint("cuTensorMapEncodeTiled", &f, cudaEnableDefault, &qr);
        fn = (PFN_encodeTiled)f;
    }
    return fn;
}
static void make_map(CUtensorMap* m, const void* base, int rank, const cuuint64_t* dims, const cuuint64_t* strides, const cuuint32_t* box, bool sw128) {
    cuuint32_t es[3] = {1, 1, 1};
    get_encode()(m, CU_TENSOR_MAP_DATA_TYPE_BFLOAT16, rank, const_cast<void*>(base), dims, strides, box, es, CU_TENSOR_MAP_INTERLEAVE_NONE,
                 sw128 ? CU_TENSOR_MAP_SWIZZLE_128B : CU_TENSOR_MAP_SWIZZLE_NONE, CU_TENSOR_MAP_L2_PROMOTION_L2_128B, CU_TENSOR_MAP_FLOAT_OOB_FILL_NONE);
}

}

extern "C" void kernel_launch(void* const* d_in, const int* in_sizes, int n_in, void* d_out, int out_size) {
    using namespace mk;
    Params p;
    p.q = (const __nv_bfloat16*)d_in[0]; p.k = (const __nv_bfloat16*)d_in[1]; p.v = (const __nv_bfloat16*)d_in[2];
    p.shift_k = (const __nv_bfloat16*)d_in[3]; p.ssm_k = (const __nv_bfloat16*)d_in[4]; p.ssm_D = (const __nv_bfloat16*)d_in[5];
    const __nv_bfloat16* w1 = (const __nv_bfloat16*)d_in[7];
    p.w2 = (const __nv_bfloat16*)d_in[8];
    p.out = (__nv_bfloat16*)d_out;
    void *xn, *w2T, *h, *tT;
    cudaGetSymbolAddress(&xn, g_xn); cudaGetSymbolAddress(&w2T, g_w2T); cudaGetSymbolAddress(&h, g_h); cudaGetSymbolAddress(&tT, g_tT);
    {
        cuuint64_t dims[2] = {640, 2048}, st[1] = {1280}; cuuint32_t box[2] = {64, 128};
        make_map(&p.tm_xn, xn, 2, dims, st, box, true);
    }
    {
        cuuint64_t dims[3] = {64, 640, 24}, st[2] = {3072, 128}; cuuint32_t box[3] = {64, 64, 3};
        make_map(&p.tm_w1, w1, 3, dims, st, box, true);
    }
    {
        cuuint64_t dims[2] = {1536, 2048}, st[1] = {3072}; cuuint32_t box[2] = {64, 64};
        make_map(&p.tm_hst, h, 2, dims, st, box, true);
    }
    {
        cuuint64_t dims[3] = {64, 2048, 24}, st[2] = {3072, 128}; cuuint32_t box[3] = {64, 128, 2};
        make_map(&p.tm_h, h, 3, dims, st, box, true);
    }
    {
        cuuint64_t dims[3] = {64, 640, 24}, st[2] = {3072, 128}; cuuint32_t box[3] = {64, 80, 2};
        make_map(&p.tm_w2T, w2T, 3, dims, st, box, true);
    }
    {
        cuuint64_t dims[2] = {640, 2048}, st[1] = {1280}; cuuint32_t box[2] = {80, 128};
        make_map(&p.tm_xn_e, xn, 2, dims, st, box, false);
        make_map(&p.tm_q_e, p.q, 2, dims, st, box, false);
        cuuint64_t dims2[2] = {2048, 640}, st2[1] = {4096}; cuuint32_t box2[2] = {128, 80};
        make_map(&p.tm_tT_e, tT, 2, dims2, st2, box2, false);
    }
    cudaFuncSetAttribute(mega_kernel, cudaFuncAttributeMaxDynamicSharedMemorySize, SM_TOTAL);
    mega_kernel<<<NCTA, NTHR, SM_TOTAL>>>(p);
}
```

```cpp
#include <cuda_runtime.h>
#include <cuda_bf16.h>
#include <cuda.h>
#include <stdint.h>

namespace mk {

constexpr int S_LEN = 2048, D_MODEL = 640, D_FF = 1536;
constexpr int NCTA = 128;
constexpr int NTHR = 384;
constexpr int CH_PER_CTA = 5;

__device__ __align__(1024) __nv_bfloat16 g_xn[S_LEN * D_MODEL];
__device__ __align__(1024) __nv_bfloat16 g_kvT[D_MODEL * S_LEN];
__device__ __align__(1024) __nv_bfloat16 g_w2T[D_MODEL * D_FF];
__device__ __align__(1024) __nv_bfloat16 g_h[S_LEN * D_FF];
__device__ __align__(1024) __nv_bfloat16 g_tT[D_MODEL * S_LEN];
constexpr int FL_XN = 0;
constexpr int FL_PREP = 16;
constexpr int FL_H = 17;
constexpr int FL_T = 33;
constexpr int FL_DONE = 41;
constexpr int FL_ERR = 42;
constexpr int FL_W2 = 43;
constexpr int NFLAGS = 44;
__device__ unsigned g_flags[NFLAGS * 32];

#define TSTAMP(i, cond) do {} while (0)
__device__ __forceinline__ uint32_t smem_u32(const void* p) { return (uint32_t)__cvta_generic_to_shared(p); }
__device__ __forceinline__ void mbar_init(uint32_t bar, uint32_t cnt) { asm volatile("mbarrier.init.shared::cta.b64 [%0], %1;" :: "r"(bar), "r"(cnt)); }
__device__ __forceinline__ void mbar_expect_tx(uint32_t bar, uint32_t bytes) { asm volatile("mbarrier.arrive.expect_tx.shared::cta.b64 _, [%0], %1;" :: "r"(bar), "r"(bytes) : "memory"); }
__device__ __forceinline__ void mbar_arrive(uint32_t bar) { asm volatile("mbarrier.arrive.shared::cta.b64 _, [%0];" :: "r"(bar) : "memory"); }
__device__ __forceinline__ void mbar_wait(uint32_t bar, uint32_t parity) {
    uint32_t ok; int it = 0;
    do {
        asm volatile("{\n.reg .pred p;\nmbarrier.try_wait.parity.shared::cta.b64 p, [%1], %2;\nselp.u32 %0, 1, 0, p;\n}\n" : "=r"(ok) : "r"(bar), "r"(parity) : "memory");
        if (++it > (1 << 22)) { g_flags[FL_ERR * 32] = 1; __trap(); }
    } while (!ok);
}
__device__ __forceinline__ void tma_load_2d(uint32_t dst, const CUtensorMap* map, int c0, int c1, uint32_t bar) {
    asm volatile("cp.async.bulk.tensor.2d.shared::cluster.global.mbarrier::complete_tx::bytes [%0], [%1, {%3, %4}], [%2];"
        :: "r"(dst), "l"(map), "r"(bar), "r"(c0), "r"(c1) : "memory");
}
__device__ __forceinline__ void tma_load_3d(uint32_t dst, const CUtensorMap* map, int c0, int c1, int c2, uint32_t bar) {
    asm volatile("cp.async.bulk.tensor.3d.shared::cluster.global.mbarrier::complete_tx::bytes [%0], [%1, {%3, %4, %5}], [%2];"
        :: "r"(dst), "l"(map), "r"(bar), "r"(c0), "r"(c1), "r"(c2) : "memory");
}
__device__ __forceinline__ void tma_store_2d(const CUtensorMap* map, uint32_t src, int c0, int c1) {
    asm volatile("cp.async.bulk.tensor.2d.global.shared::cta.bulk_group [%0, {%2, %3}], [%1];" :: "l"(map), "r"(src), "r"(c0), "r"(c1) : "memory");
}
__device__ __forceinline__ void bulk_commit() { asm volatile("cp.async.bulk.commit_group;" ::: "memory"); }
__device__ __forceinline__ void bulk_wait_all() { asm volatile("cp.async.bulk.wait_group 0;" ::: "memory"); }
__device__ __forceinline__ void fence_proxy_async() { asm volatile("fence.proxy.async;" ::: "memory"); }
__device__ __forceinline__ void fence_proxy_async_smem() { asm volatile("fence.proxy.async.shared::cta;" ::: "memory"); }
__device__ __forceinline__ void named_bar(int id, int n) { asm volatile("bar.sync %0, %1;" :: "r"(id), "r"(n) : "memory"); }
__device__ __forceinline__ void wgmma_fence() { asm volatile("wgmma.fence.sync.aligned;\n" ::: "memory"); }
__device__ __forceinline__ void wgmma_commit() { asm volatile("wgmma.commit_group.sync.aligned;\n" ::: "memory"); }
template<int N> __device__ __forceinline__ void wgmma_wait() { asm volatile("wgmma.wait_group.sync.aligned %0;\n" :: "n"(N) : "memory"); }
__device__ __forceinline__ unsigned ld_acquire(const unsigned* p) { unsigned v; asm volatile("ld.acquire.gpu.global.u32 %0, [%1];" : "=r"(v) : "l"(p) : "memory"); return v; }
__device__ __forceinline__ void wait_flag(int idx, unsigned target) {
    const unsigned* p = &g_flags[idx * 32];
    int it = 0;
    while (ld_acquire(p) < target) { if (++it > (1 << 22)) { g_flags[FL_ERR * 32] = 2; __trap(); } }
}
__device__ __forceinline__ void signal_flag(int idx) {
    __threadfence();
    atomicAdd(&g_flags[idx * 32], 1u);
}
__device__ __forceinline__ float bf2f(__nv_bfloat16 v) { return __bfloat162float(v); }
__device__ __forceinline__ float rbf(float x) { uint32_t r; asm("cvt.rn.bf16x2.f32 %0, %1, %2;" : "=r"(r) : "f"(0.f), "f"(x)); return __uint_as_float(r << 16); }
__device__ __forceinline__ uint32_t pack_bf2(float lo, float hi) { __nv_bfloat162 v = __floats2bfloat162_rn(lo, hi); return *reinterpret_cast<uint32_t*>(&v); }
__device__ __forceinline__ float bflo(uint32_t w) { return __uint_as_float(w << 16); }
__device__ __forceinline__ float bfhi(uint32_t w) { return __uint_as_float(w & 0xffff0000u); }

__device__ __forceinline__ uint32_t bmul2(uint32_t a, uint32_t b) { __nv_bfloat162 r = __hmul2_rn(*reinterpret_cast<__nv_bfloat162*>(&a), *reinterpret_cast<__nv_bfloat162*>(&b)); return *reinterpret_cast<uint32_t*>(&r); }
__device__ __forceinline__ uint32_t badd2(uint32_t a, uint32_t b) { __nv_bfloat162 r = __hadd2_rn(*reinterpret_cast<__nv_bfloat162*>(&a), *reinterpret_cast<__nv_bfloat162*>(&b)); return *reinterpret_cast<uint32_t*>(&r); }
__device__ __forceinline__ uint32_t bsub2(uint32_t a, uint32_t b) { __nv_bfloat162 r = __hsub2_rn(*reinterpret_cast<__nv_bfloat162*>(&a), *reinterpret_cast<__nv_bfloat162*>(&b)); return *reinterpret_cast<uint32_t*>(&r); }
__device__ __forceinline__ float div_by(float a, float d, float r) { float q = a * r; float e = fmaf(-q, d, a); return fmaf(e, r, q); }

__device__ __forceinline__ uint64_t desc_sw128(uint32_t addr, uint32_t lbo_bytes, uint32_t sbo_bytes) {
    return ((uint64_t)((addr & 0x3FFFF) >> 4)) | ((uint64_t)(lbo_bytes >> 4) << 16) | ((uint64_t)(sbo_bytes >> 4) << 32) | ((uint64_t)1 << 62);
}
__device__ __forceinline__ uint64_t desc_nosw(uint32_t addr, uint32_t lbo_bytes, uint32_t sbo_bytes) {
    return ((uint64_t)((addr & 0x3FFFF) >> 4)) | ((uint64_t)(lbo_bytes >> 4) << 16) | ((uint64_t)(sbo_bytes >> 4) << 32);
}

__device__ __forceinline__ void wgmma_rs_n8(float* d, uint32_t a0, uint32_t a1, uint32_t a2, uint32_t a3, uint64_t descB) {
    asm volatile("wgmma.mma_async.sync.aligned.m64n8k16.f32.bf16.bf16 {%0,%1,%2,%3}, {%4,%5,%6,%7}, %8, 1, 1, 1, 0;\n"
        : "+f"(d[0]), "+f"(d[1]), "+f"(d[2]), "+f"(d[3])
        : "r"(a0), "r"(a1), "r"(a2), "r"(a3), "l"(descB));
}
__device__ __forceinline__ void wgmma_rs_n16(float* d, uint32_t a0, uint32_t a1, uint32_t a2, uint32_t a3, uint64_t descB) {
    asm volatile("wgmma.mma_async.sync.aligned.m64n16k16.f32.bf16.bf16 {%0,%1,%2,%3,%4,%5,%6,%7}, {%8,%9,%10,%11}, %12, 1, 1, 1, 0;\n"
        : "+f"(d[0]), "+f"(d[1]), "+f"(d[2]), "+f"(d[3]), "+f"(d[4]), "+f"(d[5]), "+f"(d[6]), "+f"(d[7])
        : "r"(a0), "r"(a1), "r"(a2), "r"(a3), "l"(descB));
}
__device__ __forceinline__ void wgmma_rs_n24(float* d, uint32_t a0, uint32_t a1, uint32_t a2, uint32_t a3, uint64_t descB) {
    asm volatile("wgmma.mma_async.sync.aligned.m64n24k16.f32.bf16.bf16 {%0,%1,%2,%3,%4,%5,%6,%7,%8,%9,%10,%11}, {%12,%13,%14,%15}, %16, 1, 1, 1, 0;\n"
        : "+f"(d[0]), "+f"(d[1]), "+f"(d[2]), "+f"(d[3]), "+f"(d[4]), "+f"(d[5]), "+f"(d[6]), "+f"(d[7]), "+f"(d[8]), "+f"(d[9]), "+f"(d[10]), "+f"(d[11])
        : "r"(a0), "r"(a1), "r"(a2), "r"(a3), "l"(descB));
}
__device__ __forceinline__ void wgmma_rs_n32(float* d, uint32_t a0, uint32_t a1, uint32_t a2, uint32_t a3, uint64_t descB) {
    asm volatile("wgmma.mma_async.sync.aligned.m64n32k16.f32.bf16.bf16 {%0,%1,%2,%3,%4,%5,%6,%7,%8,%9,%10,%11,%12,%13,%14,%15}, {%16,%17,%18,%19}, %20, 1, 1, 1, 0;\n"
        : "+f"(d[0]), "+f"(d[1]), "+f"(d[2]), "+f"(d[3]), "+f"(d[4]), "+f"(d[5]), "+f"(d[6]), "+f"(d[7]), "+f"(d[8]), "+f"(d[9]), "+f"(d[10]), "+f"(d[11]), "+f"(d[12]), "+f"(d[13]), "+f"(d[14]), "+f"(d[15])
        : "r"(a0), "r"(a1), "r"(a2), "r"(a3), "l"(descB));
}
__device__ __forceinline__ void wgmma_rs_n48(float* d, uint32_t a0, uint32_t a1, uint32_t a2, uint32_t a3, uint64_t descB) {
    asm volatile("wgmma.mma_async.sync.aligned.m64n48k16.f32.bf16.bf16 {%0,%1,%2,%3,%4,%5,%6,%7,%8,%9,%10,%11,%12,%13,%14,%15,%16,%17,%18,%19,%20,%21,%22,%23}, {%24,%25,%26,%27}, %28, 1, 1, 1, 0;\n"
        : "+f"(d[0]), "+f"(d[1]), "+f"(d[2]), "+f"(d[3]), "+f"(d[4]), "+f"(d[5]), "+f"(d[6]), "+f"(d[7]), "+f"(d[8]), "+f"(d[9]), "+f"(d[10]), "+f"(d[11]), "+f"(d[12]), "+f"(d[13]), "+f"(d[14]), "+f"(d[15]), "+f"(d[16]), "+f"(d[17]), "+f"(d[18]), "+f"(d[19]), "+f"(d[20]), "+f"(d[21]), "+f"(d[22]), "+f"(d[23])
        : "r"(a0), "r"(a1), "r"(a2), "r"(a3), "l"(descB));
}
__device__ __forceinline__ void wgmma_rs_n64(float* d, uint32_t a0, uint32_t a1, uint32_t a2, uint32_t a3, uint64_t descB) {
    asm volatile("wgmma.mma_async.sync.aligned.m64n64k16.f32.bf16.bf16 {%0,%1,%2,%3,%4,%5,%6,%7,%8,%9,%10,%11,%12,%13,%14,%15,%16,%17,%18,%19,%20,%21,%22,%23,%24,%25,%26,%27,%28,%29,%30,%31}, {%32,%33,%34,%35}, %36, 1, 1, 1, 0;\n"
        : "+f"(d[0]), "+f"(d[1]), "+f"(d[2]), "+f"(d[3]), "+f"(d[4]), "+f"(d[5]), "+f"(d[6]), "+f"(d[7]), "+f"(d[8]), "+f"(d[9]), "+f"(d[10]), "+f"(d[11]), "+f"(d[12]), "+f"(d[13]), "+f"(d[14]), "+f"(d[15]), "+f"(d[16]), "+f"(d[17]), "+f"(d[18]), "+f"(d[19]), "+f"(d[20]), "+f"(d[21]), "+f"(d[22]), "+f"(d[23]), "+f"(d[24]), "+f"(d[25]), "+f"(d[26]), "+f"(d[27]), "+f"(d[28]), "+f"(d[29]), "+f"(d[30]), "+f"(d[31])
        : "r"(a0), "r"(a1), "r"(a2), "r"(a3), "l"(descB));
}
__device__ __forceinline__ void wgmma_ss_n192(float* d, uint64_t descA, uint64_t descB) {
    asm volatile("wgmma.mma_async.sync.aligned.m64n192k16.f32.bf16.bf16 {%0,%1,%2,%3,%4,%5,%6,%7,%8,%9,%10,%11,%12,%13,%14,%15,%16,%17,%18,%19,%20,%21,%22,%23,%24,%25,%26,%27,%28,%29,%30,%31,%32,%33,%34,%35,%36,%37,%38,%39,%40,%41,%42,%43,%44,%45,%46,%47,%48,%49,%50,%51,%52,%53,%54,%55,%56,%57,%58,%59,%60,%61,%62,%63,%64,%65,%66,%67,%68,%69,%70,%71,%72,%73,%74,%75,%76,%77,%78,%79,%80,%81,%82,%83,%84,%85,%86,%87,%88,%89,%90,%91,%92,%93,%94,%95}, %96, %97, 1, 1, 1, 0, 1;\n"
        : "+f"(d[0]), "+f"(d[1]), "+f"(d[2]), "+f"(d[3]), "+f"(d[4]), "+f"(d[5]), "+f"(d[6]), "+f"(d[7]), "+f"(d[8]), "+f"(d[9]), "+f"(d[10]), "+f"(d[11]), "+f"(d[12]), "+f"(d[13]), "+f"(d[14]), "+f"(d[15]), "+f"(d[16]), "+f"(d[17]), "+f"(d[18]), "+f"(d[19]), "+f"(d[20]), "+f"(d[21]), "+f"(d[22]), "+f"(d[23]), "+f"(d[24]), "+f"(d[25]), "+f"(d[26]), "+f"(d[27]), "+f"(d[28]), "+f"(d[29]), "+f"(d[30]), "+f"(d[31]), "+f"(d[32]), "+f"(d[33]), "+f"(d[34]), "+f"(d[35]), "+f"(d[36]), "+f"(d[37]), "+f"(d[38]), "+f"(d[39]), "+f"(d[40]), "+f"(d[41]), "+f"(d[42]), "+f"(d[43]), "+f"(d[44]), "+f"(d[45]), "+f"(d[46]), "+f"(d[47]), "+f"(d[48]), "+f"(d[49]), "+f"(d[50]), "+f"(d[51]), "+f"(d[52]), "+f"(d[53]), "+f"(d[54]), "+f"(d[55]), "+f"(d[56]), "+f"(d[57]), "+f"(d[58]), "+f"(d[59]), "+f"(d[60]), "+f"(d[61]), "+f"(d[62]), "+f"(d[63]), "+f"(d[64]), "+f"(d[65]), "+f"(d[66]), "+f"(d[67]), "+f"(d[68]), "+f"(d[69]), "+f"(d[70]), "+f"(d[71]), "+f"(d[72]), "+f"(d[73]), "+f"(d[74]), "+f"(d[75]), "+f"(d[76]), "+f"(d[77]), "+f"(d[78]), "+f"(d[79]), "+f"(d[80]), "+f"(d[81]), "+f"(d[82]), "+f"(d[83]), "+f"(d[84]), "+f"(d[85]), "+f"(d[86]), "+f"(d[87]), "+f"(d[88]), "+f"(d[89]), "+f"(d[90]), "+f"(d[91]), "+f"(d[92]), "+f"(d[93]), "+f"(d[94]), "+f"(d[95])
        : "l"(descA), "l"(descB));
}
__device__ __forceinline__ void wgmma_ss_n80(float* d, uint64_t descA, uint64_t descB) {
    asm volatile("wgmma.mma_async.sync.aligned.m64n80k16.f32.bf16.bf16 {%0,%1,%2,%3,%4,%5,%6,%7,%8,%9,%10,%11,%12,%13,%14,%15,%16,%17,%18,%19,%20,%21,%22,%23,%24,%25,%26,%27,%28,%29,%30,%31,%32,%33,%34,%35,%36,%37,%38,%39}, %40, %41, 1, 1, 1, 0, 0;\n"
        : "+f"(d[0]), "+f"(d[1]), "+f"(d[2]), "+f"(d[3]), "+f"(d[4]), "+f"(d[5]), "+f"(d[6]), "+f"(d[7]), "+f"(d[8]), "+f"(d[9]), "+f"(d[10]), "+f"(d[11]), "+f"(d[12]), "+f"(d[13]), "+f"(d[14]), "+f"(d[15]), "+f"(d[16]), "+f"(d[17]), "+f"(d[18]), "+f"(d[19]), "+f"(d[20]), "+f"(d[21]), "+f"(d[22]), "+f"(d[23]), "+f"(d[24]), "+f"(d[25]), "+f"(d[26]), "+f"(d[27]), "+f"(d[28]), "+f"(d[29]), "+f"(d[30]), "+f"(d[31]), "+f"(d[32]), "+f"(d[33]), "+f"(d[34]), "+f"(d[35]), "+f"(d[36]), "+f"(d[37]), "+f"(d[38]), "+f"(d[39])
        : "l"(descA), "l"(descB));
}
__device__ __forceinline__ void wgmma_ss_n64(float* d, uint64_t descA, uint64_t descB) {
    asm volatile("wgmma.mma_async.sync.aligned.m64n64k16.f32.bf16.bf16 {%0,%1,%2,%3,%4,%5,%6,%7,%8,%9,%10,%11,%12,%13,%14,%15,%16,%17,%18,%19,%20,%21,%22,%23,%24,%25,%26,%27,%28,%29,%30,%31}, %32, %33, 1, 1, 1, 0, 0;\n"
        : "+f"(d[0]), "+f"(d[1]), "+f"(d[2]), "+f"(d[3]), "+f"(d[4]), "+f"(d[5]), "+f"(d[6]), "+f"(d[7]), "+f"(d[8]), "+f"(d[9]), "+f"(d[10]), "+f"(d[11]), "+f"(d[12]), "+f"(d[13]), "+f"(d[14]), "+f"(d[15]), "+f"(d[16]), "+f"(d[17]), "+f"(d[18]), "+f"(d[19]), "+f"(d[20]), "+f"(d[21]), "+f"(d[22]), "+f"(d[23]), "+f"(d[24]), "+f"(d[25]), "+f"(d[26]), "+f"(d[27]), "+f"(d[28]), "+f"(d[29]), "+f"(d[30]), "+f"(d[31])
        : "l"(descA), "l"(descB));
}
__device__ __forceinline__ void wgmma_ss_n48(float* d, uint64_t descA, uint64_t descB) {
    asm volatile("wgmma.mma_async.sync.aligned.m64n48k16.f32.bf16.bf16 {%0,%1,%2,%3,%4,%5,%6,%7,%8,%9,%10,%11,%12,%13,%14,%15,%16,%17,%18,%19,%20,%21,%22,%23}, %24, %25, 1, 1, 1, 0, 0;\n"
        : "+f"(d[0]), "+f"(d[1]), "+f"(d[2]), "+f"(d[3]), "+f"(d[4]), "+f"(d[5]), "+f"(d[6]), "+f"(d[7]), "+f"(d[8]), "+f"(d[9]), "+f"(d[10]), "+f"(d[11]), "+f"(d[12]), "+f"(d[13]), "+f"(d[14]), "+f"(d[15]), "+f"(d[16]), "+f"(d[17]), "+f"(d[18]), "+f"(d[19]), "+f"(d[20]), "+f"(d[21]), "+f"(d[22]), "+f"(d[23])
        : "l"(descA), "l"(descB));
}
__device__ __forceinline__ void wgmma_ss_n32(float* d, uint64_t descA, uint64_t descB) {
    asm volatile("wgmma.mma_async.sync.aligned.m64n32k16.f32.bf16.bf16 {%0,%1,%2,%3,%4,%5,%6,%7,%8,%9,%10,%11,%12,%13,%14,%15}, %16, %17, 1, 1, 1, 0, 0;\n"
        : "+f"(d[0]), "+f"(d[1]), "+f"(d[2]), "+f"(d[3]), "+f"(d[4]), "+f"(d[5]), "+f"(d[6]), "+f"(d[7]), "+f"(d[8]), "+f"(d[9]), "+f"(d[10]), "+f"(d[11]), "+f"(d[12]), "+f"(d[13]), "+f"(d[14]), "+f"(d[15])
        : "l"(descA), "l"(descB));
}
__device__ __forceinline__ void wgmma_ss_n16(float* d, uint64_t descA, uint64_t descB) {
    asm volatile("wgmma.mma_async.sync.aligned.m64n16k16.f32.bf16.bf16 {%0,%1,%2,%3,%4,%5,%6,%7}, %8, %9, 1, 1, 1, 0, 0;\n"
        : "+f"(d[0]), "+f"(d[1]), "+f"(d[2]), "+f"(d[3]), "+f"(d[4]), "+f"(d[5]), "+f"(d[6]), "+f"(d[7])
        : "l"(descA), "l"(descB));
}

constexpr int SM_PIPE = 0;
constexpr int ST1_BYTES = 40960, ST1_N = 4;
constexpr int ST2_BYTES = 53248, ST2_N = 3;
constexpr int SM_CU = 2 * ST2_BYTES;
constexpr int SM_CT = SM_CU + 2 * 18432;
constexpr int SM_X = 163840;
constexpr int SM_U = SM_X;
constexpr int F_COPY1 = 4224 + 64;
constexpr int F_BYTES = F_COPY1 + 4224;
constexpr int SM_F = SM_X + 2 * 13824;
constexpr int SM_BAR = SM_F + 2 * F_BYTES;
constexpr int SM_TOTAL = SM_BAR + 256;
constexpr int B_FULL1 = 0, B_EMPTY1 = 4, B_FULL2 = 8, B_EMPTY2 = 11, B_G1DONE = 14, B_CONVDONE = 15, B_HSTG = 16, B_W2DONE = 18;

struct Params {
    CUtensorMap tm_xn, tm_w1, tm_hst, tm_h, tm_w2T, tm_xn_e, tm_q_e, tm_tT_e, tm_out;
    const __nv_bfloat16 *q, *k, *v, *shift_k, *ssm_k, *ssm_D, *w2;
    __nv_bfloat16* out;
};

#define SKIP_KV 0
#define SKIP_KVST 0
#define SKIP_W2 0
__device__ __forceinline__ void prep_w2T(const Params& p, uint8_t* smem, int cta, uint32_t bar_w2done) {
    const int lane = threadIdx.x & 31;
        const int k0 = (cta >> 3) * 96, n0 = (cta & 7) * 80;
        uint8_t* stg = smem + SM_U;
        #pragma unroll 1
        for (int bt = 0; bt < (SKIP_W2 ? 0 : 3); bt++) {
            uint4 vv[10];
            #pragma unroll
            for (int it = 0; it < 10; it++) {
                const int idx = lane + 32 * (bt * 10 + it);
                const int r = idx / 10, c = idx % 10;
                vv[it] = *reinterpret_cast<const uint4*>(p.w2 + (size_t)(k0 + r) * D_MODEL + n0 + c * 8);
            }
            #pragma unroll
            for (int it = 0; it < 10; it++) {
                const int idx = lane + 32 * (bt * 10 + it);
                const int r = idx / 10, c = idx % 10;
                uint32_t w[4] = {vv[it].x, vv[it].y, vv[it].z, vv[it].w};
                #pragma unroll
                for (int e = 0; e < 4; e++) {
                    *reinterpret_cast<uint16_t*>(stg + (c * 8 + 2 * e) * 208 + r * 2) = (uint16_t)(w[e] & 0xffffu);
                    *reinterpret_cast<uint16_t*>(stg + (c * 8 + 2 * e + 1) * 208 + r * 2) = (uint16_t)(w[e] >> 16);
                }
            }
        }
        __syncwarp();
        #pragma unroll 1
        for (int bt = 0; bt < (SKIP_W2 ? 0 : 3); bt++) {
            #pragma unroll
            for (int it = 0; it < 10; it++) {
                const int idx = lane + 32 * (bt * 10 + it);
                const int n = idx / 12, c = idx % 12;
                uint4 v4 = *reinterpret_cast<const uint4*>(stg + n * 208 + c * 16);
                *reinterpret_cast<uint4*>(g_w2T + (size_t)(n0 + n) * D_FF + k0 + c * 8) = v4;
            }
        }
        __syncwarp();
        if (lane == 0) { mbar_arrive(bar_w2done); __threadfence(); atomicAdd(&g_flags[FL_W2 * 32], 1u); }
}
__device__ __forceinline__ void prep_phase(const Params& p, uint8_t* smem, int cta) {
    const int tid = threadIdx.x, warp = tid >> 5, lane = tid & 31;
    const int s0 = cta * 16;
    if (warp < 8) {
        uint32_t w[2][10];
        #pragma unroll
        for (int rr = 0; rr < 2; rr++) {
            const __nv_bfloat16* xr = p.q + (size_t)(s0 + warp * 2 + rr) * D_MODEL;
            uint4 a = *reinterpret_cast<const uint4*>(xr + lane * 8);
            uint4 b = *reinterpret_cast<const uint4*>(xr + 256 + lane * 8);
            uint2 c = *reinterpret_cast<const uint2*>(xr + 512 + lane * 4);
            w[rr][0] = a.x; w[rr][1] = a.y; w[rr][2] = a.z; w[rr][3] = a.w; w[rr][4] = b.x; w[rr][5] = b.y; w[rr][6] = b.z; w[rr][7] = b.w; w[rr][8] = c.x; w[rr][9] = c.y;
        }
        #pragma unroll 1
        for (int rr = 0; rr < 2; rr++) {
            uint32_t wr[10];
            #pragma unroll
            for (int i = 0; i < 10; i++) wr[i] = rr ? w[1][i] : w[0][i];
            float x[20];
            #pragma unroll
            for (int i = 0; i < 10; i++) { x[2 * i] = bflo(wr[i]); x[2 * i + 1] = bfhi(wr[i]); }
            float sum = 0.f;
            #pragma unroll
            for (int i = 0; i < 20; i++) sum += x[i];
            #pragma unroll
            for (int o = 16; o > 0; o >>= 1) sum += __shfl_xor_sync(0xffffffffu, sum, o);
            const float mean = sum * (1.0f / 640.0f);
            float sq = 0.f;
            #pragma unroll
            for (int i = 0; i < 20; i++) { float dd = x[i] - mean; sq += dd * dd; }
            #pragma unroll
            for (int o = 16; o > 0; o >>= 1) sq += __shfl_xor_sync(0xffffffffu, sq, o);
            const float var_b = rbf(sq * (1.0f / 640.0f));
            const uint32_t m2 = pack_bf2(mean, mean);
            const float den = rbf(__fsqrt_rn(rbf(var_b + 1e-5f)));
            const float rden = __frcp_rn(den);
            uint32_t o[10];
            #pragma unroll
            for (int i = 0; i < 10; i++) {
                const uint32_t c2 = bsub2(wr[i], m2);
                o[i] = pack_bf2(div_by(bflo(c2), den, rden), div_by(bfhi(c2), den, rden));
            }
            __nv_bfloat16* yr = g_xn + (size_t)(s0 + warp * 2 + rr) * D_MODEL;
            *reinterpret_cast<uint4*>(yr + lane * 8) = make_uint4(o[0], o[1], o[2], o[3]);
            *reinterpret_cast<uint4*>(yr + 256 + lane * 8) = make_uint4(o[4], o[5], o[6], o[7]);
            *reinterpret_cast<uint2*>(yr + 512 + lane * 4) = make_uint2(o[8], o[9]);
        }
        named_bar(1, 256);
        if (tid == 0) { __threadfence(); atomicAdd(&g_flags[(FL_XN + (cta >> 3)) * 32], 1u); }
        __syncwarp();
        asm volatile("bar.arrive 5, 384;" ::: "memory");
    } else {
        const int t = tid - 256;
        const int half = t & 1;
        uint32_t kw[5][11], vw[5][8]; uint4 sk[5];
        #pragma unroll
        for (int it = 0; it < 5; it++) {
            const int d = 2 * ((t >> 1) + 64 * it);
            const int r0 = s0 + 8 * half;
            sk[it] = *reinterpret_cast<const uint4*>(p.shift_k + d * 4);
            #pragma unroll
            for (int j = 0; j < 11; j++) {
                const int row = r0 - 3 + j;
                kw[it][j] = (row >= 0) ? *reinterpret_cast<const uint32_t*>(p.k + (size_t)row * D_MODEL + d) : 0u;
            }
            #pragma unroll
            for (int j = 0; j < 8; j++) vw[it][j] = *reinterpret_cast<const uint32_t*>(p.v + (size_t)(r0 + j) * D_MODEL + d);
        }
        uint32_t o0[5][4], o1[5][4];
        #pragma unroll
        for (int it = 0; it < 5; it++) {
            const uint32_t W0 = __byte_perm(sk[it].x, sk[it].z, 0x5410), W1 = __byte_perm(sk[it].x, sk[it].z, 0x7632);
            const uint32_t W2 = __byte_perm(sk[it].y, sk[it].w, 0x5410), W3 = __byte_perm(sk[it].y, sk[it].w, 0x7632);
            uint32_t r[8];
            #pragma unroll
            for (int j = 0; j < 8; j++) {
                uint32_t a = bmul2(kw[it][j], W3);
                a = badd2(a, bmul2(kw[it][j + 1], W2));
                a = badd2(a, bmul2(kw[it][j + 2], W1));
                a = badd2(a, bmul2(kw[it][j + 3], W0));
                r[j] = bmul2(a, vw[it][j]);
            }
            #pragma unroll
            for (int j = 0; j < 4; j++) { o0[it][j] = __byte_perm(r[2 * j], r[2 * j + 1], 0x5410); o1[it][j] = __byte_perm(r[2 * j], r[2 * j + 1], 0x7632); }
        }
        named_bar(5, 384);
        #pragma unroll
        for (int it = 0; it < 5; it++) {
            const int d = 2 * ((t >> 1) + 64 * it);
            *reinterpret_cast<uint4*>(g_kvT + (size_t)d * S_LEN + s0 + 8 * half) = make_uint4(o0[it][0], o0[it][1], o0[it][2], o0[it][3]);
            *reinterpret_cast<uint4*>(g_kvT + (size_t)(d + 1) * S_LEN + s0 + 8 * half) = make_uint4(o1[it][0], o1[it][1], o1[it][2], o1[it][3]);
        }
        named_bar(3, 128);
        if (t == 0) { __threadfence(); atomicAdd(&g_flags[FL_PREP * 32], 1u); }
    }
}

__device__ __forceinline__ void stmatrix_x4(uint32_t addr, uint32_t r0, uint32_t r1, uint32_t r2, uint32_t r3) {
    asm volatile("stmatrix.sync.aligned.m8n8.x4.shared.b16 [%0], {%1, %2, %3, %4};" :: "r"(addr), "r"(r0), "r"(r1), "r"(r2), "r"(r3) : "memory");
}
__device__ __forceinline__ uint32_t lds32(uint32_t addr) { uint32_t v; asm volatile("ld.shared.u32 %0, [%1];" : "=r"(v) : "r"(addr)); return v; }

constexpr int UST = 1152;
constexpr int UCOPY = 4 * UST;
constexpr int UBUF = 4 * UCOPY;
template<int E>
__device__ __forceinline__ void conv_mma2(float* acc, const uint32_t (&A)[8], uint64_t descB) {
    #pragma unroll
    for (int kk = 0; kk < 2; kk++) {
        const uint64_t db = descB + (uint64_t)((2 * kk * UST) >> 4);
        if (E == 0) wgmma_rs_n64(acc, A[4 * kk], A[4 * kk + 1], A[4 * kk + 2], A[4 * kk + 3], db);
        if (E == 1) wgmma_rs_n48(acc, A[4 * kk], A[4 * kk + 1], A[4 * kk + 2], A[4 * kk + 3], db);
        if (E == 2) wgmma_rs_n32(acc, A[4 * kk], A[4 * kk + 1], A[4 * kk + 2], A[4 * kk + 3], db);
        if (E == 3) wgmma_rs_n16(acc, A[4 * kk], A[4 * kk + 1], A[4 * kk + 2], A[4 * kk + 3], db);
    }
}
__device__ __forceinline__ uint32_t swap16(uint32_t x) { uint32_t r; asm volatile("prmt.b32 %0, %1, 0, 0x1032;" : "=r"(r) : "r"(x)); return r; }
__device__ __forceinline__ void conv_ldP(uint32_t (&P)[5], uint32_t pfa, int s) {
    #pragma unroll
    for (int j = 0; j < 5; j++) P[j] = lds32(pfa + s * 128 + j * 16);
}
__device__ __forceinline__ void conv_mkA(uint32_t (&A)[8], const uint32_t (&P)[5]) {
    A[0] = swap16(P[3]); A[1] = swap16(P[4]); A[2] = swap16(P[2]); A[3] = swap16(P[3]);
    A[4] = swap16(P[1]); A[5] = swap16(P[2]); A[6] = swap16(P[0]); A[7] = swap16(P[1]);
}
__host__ __device__ constexpr int conv_step_of(int i) { return 8 * (i & 3) + (i >> 2); }
template<int I> struct ConvStep {
    __device__ static __forceinline__ void run(float* acc0, float* acc1, float* acc2, float* acc3, uint32_t (&A)[3][8], uint32_t (&P)[5], uint32_t pfa, uint32_t ubs) {
        if (I + 1 < 32) conv_mkA(A[(I + 1) % 3], P);
        if (I + 2 < 32) conv_ldP(P, pfa, conv_step_of(I + 2));
        constexpr int r = I >> 2;
        const uint64_t db = desc_nosw(ubs + (r & 3) * UCOPY + ((r >> 2) ? 0 : 128), UST, 128);
        wgmma_fence();
        if ((I & 3) == 0) conv_mma2<0>(acc0, A[I % 3], db);
        if ((I & 3) == 1) conv_mma2<1>(acc1, A[I % 3], db);
        if ((I & 3) == 2) conv_mma2<2>(acc2, A[I % 3], db);
        if ((I & 3) == 3) conv_mma2<3>(acc3, A[I % 3], db);
        wgmma_commit();
        wgmma_wait<1>();
        ConvStep<I + 1>::run(acc0, acc1, acc2, acc3, A, P, pfa, ubs);
    }
};
template<> struct ConvStep<32> { __device__ static __forceinline__ void run(float*, float*, float*, float*, uint32_t (&)[3][8], uint32_t (&)[5], uint32_t, uint32_t) {} };

#define EARLY_B 0
__global__ void __launch_bounds__(NTHR, 1) mega_kernel(const __grid_constant__ Params p) {
    extern __shared__ __align__(1024) uint8_t smem[];
    const int tid = threadIdx.x, warp = tid >> 5, lane = tid & 31;
    const int cta = blockIdx.x;
    const int tb = cta >> 3, ns = cta & 7;
    const uint32_t sbase = smem_u32(smem);
    const uint32_t bar0 = sbase + SM_BAR;
    #define BAR(i) (bar0 + (i) * 8)
    TSTAMP(15, tid == 0);

    if (tid == 0) {
        for (int i = 0; i < ST1_N; i++) { mbar_init(BAR(B_FULL1 + i), 1); mbar_init(BAR(B_EMPTY1 + i), 2); }
        for (int i = 0; i < ST2_N; i++) { mbar_init(BAR(B_FULL2 + i), 1); mbar_init(BAR(B_EMPTY2 + i), 2); }
        mbar_init(BAR(B_G1DONE), 1); mbar_init(BAR(B_CONVDONE), 2); mbar_init(BAR(B_HSTG), 1); mbar_init(BAR(B_W2DONE), 1); mbar_init(BAR(B_HSTG + 1), 1);
        asm volatile("fence.mbarrier_init.release.cluster;" ::: "memory");
    }
    __syncthreads();
    if (warp == 8) {
        const void* ptr = nullptr;
        switch (lane) {
            case 0: ptr = g_xn + (size_t)cta * 16 * D_MODEL; break;
            case 1: ptr = g_kvT + (size_t)cta * CH_PER_CTA * S_LEN; break;
            case 2: ptr = g_h + (size_t)(tb * 128) * D_FF + ns * 192; break;
            case 3: ptr = g_tT + (size_t)cta * CH_PER_CTA * S_LEN; break;
            case 4: ptr = g_w2T + (size_t)(ns * 80) * D_FF; break;
            case 5: ptr = g_flags; break;
            case 6: ptr = p.out + (size_t)(tb * 128) * D_MODEL; break;
            case 7: ptr = p.ssm_k + (size_t)cta * CH_PER_CTA * S_LEN; break;
            case 8: ptr = p.ssm_D; break;
            case 9: ptr = p.w2; break;
            default: break;
        }
        if (ptr) { uint32_t dummy; asm volatile("ld.global.u32 %0, [%1];" : "=r"(dummy) : "l"(ptr)); }
    }
    if (EARLY_B && warp == 8 && lane == 0) {
        for (int kb = 0; kb < ST1_N; kb++) {
            mbar_expect_tx(BAR(B_FULL1 + kb), ST1_BYTES);
            tma_load_3d(sbase + SM_PIPE + kb * ST1_BYTES + 16384, &p.tm_w1, 0, kb * 64, ns * 3, BAR(B_FULL1 + kb));
        }
    }
    prep_phase(p, smem, cta);
    if (warp == 9) prep_w2T(p, smem, cta, BAR(B_W2DONE));
    TSTAMP(0, tid == 0);

    if (warp >= 8) {
        if (warp == 9 && lane == 0) {
            #pragma unroll
            for (int hf = 0; hf < 2; hf++) {
                mbar_wait(BAR(B_HSTG + hf), 0);
                #pragma unroll
                for (int nb = 0; nb < 3; nb++)
                    tma_store_2d(&p.tm_hst, sbase + SM_PIPE + nb * 16384 + hf * 8192, ns * 192 + nb * 64, tb * 128 + hf * 64);
                bulk_commit();
            }
            bulk_wait_all();
            mbar_arrive(BAR(B_G1DONE));
            __threadfence();
            atomicAdd(&g_flags[(FL_H + tb) * 32], 2u);
        }
        if (warp == 8 && lane == 0) {
            wait_flag(FL_XN + tb, 8);
            fence_proxy_async();
            for (int kb = 0; kb < 10; kb++) {
                const int s = kb % ST1_N;
                if (kb >= ST1_N) mbar_wait(BAR(B_EMPTY1 + s), ((kb / ST1_N) - 1) & 1);
                const uint32_t st = sbase + SM_PIPE + s * ST1_BYTES;
                if (!EARLY_B || kb >= ST1_N) mbar_expect_tx(BAR(B_FULL1 + s), ST1_BYTES);
                tma_load_2d(st, &p.tm_xn, kb * 64, tb * 128, BAR(B_FULL1 + s));
                if (!EARLY_B || kb >= ST1_N) tma_load_3d(st + 16384, &p.tm_w1, 0, kb * 64, ns * 3, BAR(B_FULL1 + s));
            }
            mbar_wait(BAR(B_G1DONE), 0);
            wait_flag(FL_W2, NCTA);
            wait_flag(FL_H + tb, 16);
            fence_proxy_async();
            for (int it = 0; it < 12; it++) {
                const int s = it % ST2_N;
                if (it >= ST2_N) mbar_wait(BAR(B_EMPTY2 + s), ((it / ST2_N) - 1) & 1);
                if (it == 2) mbar_wait(BAR(B_CONVDONE), 0);
                const uint32_t st = sbase + SM_PIPE + s * ST2_BYTES;
                mbar_expect_tx(BAR(B_FULL2 + s), ST2_BYTES);
                tma_load_3d(st, &p.tm_h, 0, tb * 128, it * 2, BAR(B_FULL2 + s));
                tma_load_3d(st + 32768, &p.tm_w2T, 0, ns * 80, it * 2, BAR(B_FULL2 + s));
            }
            mbar_wait(BAR(B_EMPTY2 + 0), ((12 / ST2_N) - 1) & 1);
            mbar_expect_tx(BAR(B_FULL2 + 0), 2 * 20480);
            tma_load_2d(sbase + SM_PIPE, &p.tm_xn_e, ns * 80, tb * 128, BAR(B_FULL2 + 0));
            tma_load_2d(sbase + SM_PIPE + 20480, &p.tm_q_e, ns * 80, tb * 128, BAR(B_FULL2 + 0));
            mbar_wait(BAR(B_EMPTY2 + 1), ((13 / ST2_N) - 1) & 1);
            wait_flag(FL_T + ns, 16);
            fence_proxy_async();
            mbar_expect_tx(BAR(B_FULL2 + 1), 20480);
            tma_load_2d(sbase + SM_PIPE + ST2_BYTES, &p.tm_tT_e, tb * 128, ns * 80, BAR(B_FULL2 + 1));
            tma_load_2d(sbase + SM_PIPE + ST2_BYTES + 10240, &p.tm_tT_e, tb * 128 + 64, ns * 80, BAR(B_FULL2 + 1));
        }
    } else {
        const int wg = warp >> 2;
        const int w = warp & 3;
        const int wt = tid & 127;
        const int g = lane >> 2, q = lane & 3;
        {
            float acc[96];
            #pragma unroll
            for (int i = 0; i < 96; i++) acc[i] = 0.f;
            for (int kb = 0; kb < 10; kb++) {
                const int s = kb % ST1_N;
                mbar_wait(BAR(B_FULL1 + s), (kb / ST1_N) & 1);
                const uint32_t sa = sbase + SM_PIPE + s * ST1_BYTES + wg * 8192;
                const uint32_t sb = sbase + SM_PIPE + s * ST1_BYTES + 16384;
                wgmma_fence();
                #pragma unroll
                for (int kk = 0; kk < 4; kk++)
                    wgmma_ss_n192(acc, desc_sw128(sa + kk * 32, 16, 1024), desc_sw128(sb + kk * 2048, 8192, 1024));
                wgmma_commit();
                wgmma_wait<0>();
                if (wt == 0) mbar_arrive(BAR(B_EMPTY1 + s));
            }
            TSTAMP(1, tid == 0);
            named_bar(1, 256);
            const uint32_t stg = sbase + SM_PIPE;
            const int m = lane >> 3, r = lane & 7;
            const int row = 16 * w + (m & 1) * 8 + r;
            #pragma unroll
            for (int j2 = 0; j2 < 12; j2++) {
                const int nb = j2 >> 2, cb = (2 * j2) & 7;
                uint32_t r0 = pack_bf2(fmaxf(acc[8 * j2 + 0], 0.f), fmaxf(acc[8 * j2 + 1], 0.f));
                uint32_t r1 = pack_bf2(fmaxf(acc[8 * j2 + 2], 0.f), fmaxf(acc[8 * j2 + 3], 0.f));
                uint32_t r2 = pack_bf2(fmaxf(acc[8 * j2 + 4], 0.f), fmaxf(acc[8 * j2 + 5], 0.f));
                uint32_t r3 = pack_bf2(fmaxf(acc[8 * j2 + 6], 0.f), fmaxf(acc[8 * j2 + 7], 0.f));
                const int chunk = cb + (m >> 1);
                stmatrix_x4(stg + nb * 16384 + wg * 8192 + row * 128 + ((chunk ^ (row & 7)) << 4), r0, r1, r2, r3);
            }
            fence_proxy_async_smem();
            named_bar(2 + wg, 128);
            if (wt == 0) mbar_arrive(BAR(B_HSTG + wg));
        }
        TSTAMP(2, tid == 0);
        {
            uint8_t* ub = smem + SM_CU + wg * UBUF;
            uint8_t* fb = smem + SM_F + wg * F_BYTES;
            float* X = reinterpret_cast<float*>(smem + SM_X + wg * 13824);
            uint8_t* Tst = smem + SM_CT + wg * 4096;
            named_bar(1, 256);
            for (int i = wt; i < 4 * 4 * 16; i += 128) {
                const int rho = i >> 6, st = (i >> 4) & 3, rr = i & 15;
                if (rr < 8 + 2 * rho) *reinterpret_cast<uint4*>(ub + rho * UCOPY + st * UST + rr * 16) = make_uint4(0, 0, 0, 0);
            }
            if (wt < 16) {
                const int cp = (wt >> 3) & 1, rr = wt & 7;
                *reinterpret_cast<uint4*>(fb + cp * F_COPY1 + rr * 16) = make_uint4(0, 0, 0, 0);
            }
            if (wt == 0) { wait_flag(FL_PREP, NCTA); mbar_wait(BAR(B_W2DONE), 0); }
            named_bar(2 + wg, 128);
            TSTAMP(3, tid == 0);
            const int d0 = cta * CH_PER_CTA;
            const int nch = (wg == 0) ? 3 : 2;
            uint4 pu[2], pf[2]; uint32_t pprev[2]; __nv_bfloat16 pD;
            auto gload = [&](int d) {
                pD = p.ssm_D[d];
                #pragma unroll
                for (int j = 0; j < 2; j++) {
                    const int idx = wt + 128 * j;
                    pu[j] = *reinterpret_cast<const uint4*>(g_kvT + (size_t)d * S_LEN + (idx & 63) * 32 + (idx >> 6) * 8);
                    pf[j] = *reinterpret_cast<const uint4*>(p.ssm_k + (size_t)d * S_LEN + idx * 8);
                    pprev[j] = (idx > 0) ? (uint32_t)*reinterpret_cast<const uint16_t*>(p.ssm_k + (size_t)d * S_LEN + idx * 8 - 1) : 0u;
                }
            };
            gload(d0 + wg);
            if (wg == 1) asm volatile("bar.arrive 6, 256;" ::: "memory");
            const uint32_t pf_off = (g & 1) ? (128 + 2 * (g - 1 - 2 * q)) : (F_COPY1 + 128 + 2 * (g - 2 * q));
            const uint32_t pfa = smem_u32(fb) + pf_off + 32 * w - 3 * 16;
            const uint32_t ubs = smem_u32(ub);
            for (int ci = 0; ci < nch; ci++) {
                const int d = d0 + 2 * ci + wg;
                #pragma unroll
                for (int j = 0; j < 2; j++) {
                    const int idx = wt + 128 * j;
                    const int a = idx & 63, kg = idx >> 6;
                    #pragma unroll
                    for (int rho = 0; rho < 4; rho++)
                        if (a + 8 + 2 * rho < 72) *reinterpret_cast<uint4*>(ub + rho * UCOPY + kg * UST + (a + 8 + 2 * rho) * 16) = pu[j];
                    *reinterpret_cast<uint4*>(fb + 128 + idx * 16) = pf[j];
                    *reinterpret_cast<uint4*>(fb + F_COPY1 + 128 + idx * 16) =
                        make_uint4(__byte_perm(pprev[j], pf[j].x, 0x5410), __byte_perm(pf[j].x, pf[j].y, 0x5432), __byte_perm(pf[j].y, pf[j].z, 0x5432), __byte_perm(pf[j].z, pf[j].w, 0x5432));
                }
                const float Dd = bf2f(pD);
                fence_proxy_async_smem();
                named_bar(2 + wg, 128);
                if (ci + 1 < nch) gload(d + 2);
                TSTAMP(8, tid == 0 && ci == 0);
                float acc0[32], acc1[24], acc2[16], acc3[8];
                #pragma unroll
                for (int i = 0; i < 32; i++) acc0[i] = 0.f;
                #pragma unroll
                for (int i = 0; i < 24; i++) acc1[i] = 0.f;
                #pragma unroll
                for (int i = 0; i < 16; i++) acc2[i] = 0.f;
                #pragma unroll
                for (int i = 0; i < 8; i++) acc3[i] = 0.f;
                named_bar(6 + wg, 256);
                TSTAMP(10 + ci, tid == 0);
                {
                    uint32_t A[3][8], P[5];
                    conv_ldP(P, pfa, conv_step_of(0)); conv_mkA(A[0], P); conv_ldP(P, pfa, conv_step_of(1));
                    ConvStep<0>::run(acc0, acc1, acc2, acc3, A, P, pfa, ubs);
                    wgmma_wait<0>();
                }
                if (!(wg == 0 && ci == 2)) asm volatile("bar.arrive %0, 256;" :: "r"(7 - wg) : "memory");
                #pragma unroll
                for (int i = 0; i < 32; i++) {
                    float v = acc0[i];
                    if (i >= 8) v += acc1[i - 8];
                    if (i >= 16) v += acc2[i - 16];
                    if (i >= 24) v += acc3[i - 24];
                    acc0[i] = v;
                }
                TSTAMP(9, tid == 0 && ci == 0);
                const int bl = 16 * (w & 1) + g;
                float* X1 = X;
                float* X0 = X + 64 * 36;
                if (w >= 2) {
                    #pragma unroll
                    for (int i = 0; i < 32; i++) { const int col = 8 * (i >> 2) + 2 * q + (i & 1); if (col < 63) X1[(col + 1) * 36 + bl + ((i >> 1) & 1) * 8] = acc0[i]; }
                } else {
                    #pragma unroll
                    for (int i = 16; i < 32; i++) X0[(8 * (i >> 2) + 2 * q + (i & 1) - 32) * 36 + bl + ((i >> 1) & 1) * 8] = acc0[i];
                }

                named_bar(2 + wg, 128);

                __nv_bfloat16* T = reinterpret_cast<__nv_bfloat16*>(Tst);
                float yv[16], uv[16];
                #pragma unroll
                for (int i = 0; i < 16; i++) {
                    const int b = bl + ((i >> 1) & 1) * 8;
                    const int a = 8 * (i >> 2) + 2 * q + (i & 1) + ((w < 2) ? 0 : 32);
                    if (w < 2) yv[i] = acc0[i] + ((a > 0) ? X1[a * 36 + b] : 0.f);
                    else yv[i] = X0[(a - 32) * 36 + b] + X1[a * 36 + b];
                    uv[i] = bf2f(*reinterpret_cast<const __nv_bfloat16*>(ub + (b >> 3) * UST + (a + 8) * 16 + (b & 7) * 2));
                }
                #pragma unroll
                for (int i = 0; i < 16; i++) {
                    const int b = bl + ((i >> 1) & 1) * 8;
                    const int a = 8 * (i >> 2) + 2 * q + (i & 1) + ((w < 2) ? 0 : 32);
                    T[32 * a + b] = __float2bfloat16_rn(rbf(yv[i]) + rbf(uv[i] * Dd));
                }

                named_bar(2 + wg, 128);

                #pragma unroll
                for (int j = 0; j < 2; j++)
                    *reinterpret_cast<uint4*>(g_tT + (size_t)d * S_LEN + (wt + 128 * j) * 8) = *reinterpret_cast<const uint4*>(Tst + (wt + 128 * j) * 16);

            }
            named_bar(1, 256);
            if (wt == 0) mbar_arrive(BAR(B_CONVDONE));
            if (tid == 0) signal_flag(FL_T + (cta >> 4));
        }
        TSTAMP(4, tid == 0);
        {
            float acc[40];
            #pragma unroll
            for (int i = 0; i < 40; i++) acc[i] = 0.f;
            for (int it = 0; it < 12; it++) {
                const int s = it % ST2_N;
                mbar_wait(BAR(B_FULL2 + s), (it / ST2_N) & 1);
                const uint32_t st = sbase + SM_PIPE + s * ST2_BYTES;
                wgmma_fence();
                #pragma unroll
                for (int kb2 = 0; kb2 < 2; kb2++)
                    #pragma unroll
                    for (int kk = 0; kk < 4; kk++)
                        wgmma_ss_n80(acc, desc_sw128(st + kb2 * 16384 + wg * 8192 + kk * 32, 16, 1024), desc_sw128(st + 32768 + kb2 * 10240 + kk * 32, 16, 1024));
                wgmma_commit();
                wgmma_wait<0>();
                if (wt == 0) mbar_arrive(BAR(B_EMPTY2 + s));
            }
            TSTAMP(5, tid == 0);
            mbar_wait(BAR(B_FULL2 + 0), (12 / ST2_N) & 1);
            mbar_wait(BAR(B_FULL2 + 1), (13 / ST2_N) & 1);
            TSTAMP(6, tid == 0);
            uint8_t* xn_t = smem + SM_PIPE;
            const uint8_t* q_t = smem + SM_PIPE + 20480;
            const uint32_t tT_t = sbase + SM_PIPE + ST2_BYTES + wg * 10240;
            uint32_t tw[20];
            {
                const int mi = lane >> 3, r = lane & 7;
                #pragma unroll
                for (int j2 = 0; j2 < 5; j2++) {
                    const int ch = 8 * (2 * j2 + (mi >> 1)) + r;
                    const int c = 2 * w + (mi & 1);
                    asm volatile("ldmatrix.sync.aligned.m8n8.x4.trans.shared.b16 {%0,%1,%2,%3}, [%4];"
                        : "=r"(tw[4 * j2]), "=r"(tw[4 * j2 + 1]), "=r"(tw[4 * j2 + 2]), "=r"(tw[4 * j2 + 3])
                        : "r"(tT_t + ch * 128 + ((c ^ (ch & 7)) << 4)));
                }
            }
            #pragma unroll
            for (int hh = 0; hh < 2; hh++) {
                const int row = 64 * wg + 16 * w + g + 8 * hh;
                uint32_t xw[10], qw[10], res[10];
                #pragma unroll
                for (int j = 0; j < 10; j++) {
                    xw[j] = *reinterpret_cast<const uint32_t*>(xn_t + row * 160 + (8 * j + 2 * q) * 2);
                    qw[j] = *reinterpret_cast<const uint32_t*>(q_t + row * 160 + (8 * j + 2 * q) * 2);
                }
                #pragma unroll
                for (int j = 0; j < 10; j++) {
                    const uint32_t tp = tw[2 * j + hh];
                    const uint32_t o2 = pack_bf2(acc[4 * j + 2 * hh], acc[4 * j + 2 * hh + 1]);
                    const float o0 = bflo(o2), o1 = bfhi(o2);
                    const uint32_t g2 = pack_bf2(__fdividef(o0, 1.0f + __expf(-o0)), __fdividef(o1, 1.0f + __expf(-o1)));
                    res[j] = badd2(qw[j], bmul2(bmul2(xw[j], tp), g2));
                }
                #pragma unroll
                for (int j = 0; j < 10; j++) *reinterpret_cast<uint32_t*>(xn_t + row * 160 + (8 * j + 2 * q) * 2) = res[j];
            }
            fence_proxy_async_smem();
            named_bar(2 + wg, 128);
            if (wt == 0) {
                tma_store_2d(&p.tm_out, sbase + SM_PIPE + wg * 64 * 160, ns * 80, tb * 128 + wg * 64);
                bulk_commit();
                bulk_wait_all();
            }
        }
    }
    __syncthreads();
    TSTAMP(7, tid == 0);
    if (tid == 0) {
        __threadfence();
        const unsigned dn = atomicAdd(&g_flags[FL_DONE * 32], 1u);
        if (dn == NCTA - 1) {
            for (int i = 0; i < NFLAGS; i++) g_flags[i * 32] = 0;
            __threadfence();
        }
    }
}

typedef CUresult (*PFN_encodeTiled)(CUtensorMap*, CUtensorMapDataType, cuuint32_t, void*, const cuuint64_t*, const cuuint64_t*, const cuuint32_t*, const cuuint32_t*,
                                    CUtensorMapInterleave, CUtensorMapSwizzle, CUtensorMapL2promotion, CUtensorMapFloatOOBfill);
static PFN_encodeTiled get_encode() {
    static PFN_encodeTiled fn = nullptr;
    if (!fn) {
        void* f = nullptr; cudaDriverEntryPointQueryResult qr;
        cudaGetDriverEntryPoint("cuTensorMapEncodeTiled", &f, cudaEnableDefault, &qr);
        fn = (PFN_encodeTiled)f;
    }
    return fn;
}
static void make_map(CUtensorMap* m, const void* base, int rank, const cuuint64_t* dims, const cuuint64_t* strides, const cuuint32_t* box, bool sw128) {
    cuuint32_t es[3] = {1, 1, 1};
    get_encode()(m, CU_TENSOR_MAP_DATA_TYPE_BFLOAT16, rank, const_cast<void*>(base), dims, strides, box, es, CU_TENSOR_MAP_INTERLEAVE_NONE,
                 sw128 ? CU_TENSOR_MAP_SWIZZLE_128B : CU_TENSOR_MAP_SWIZZLE_NONE, CU_TENSOR_MAP_L2_PROMOTION_L2_128B, CU_TENSOR_MAP_FLOAT_OOB_FILL_NONE);
}

}

extern "C" void kernel_launch(void* const* d_in, const int* in_sizes, int n_in, void* d_out, int out_size) {
    using namespace mk;
    Params p;
    p.q = (const __nv_bfloat16*)d_in[0]; p.k = (const __nv_bfloat16*)d_in[1]; p.v = (const __nv_bfloat16*)d_in[2];
    p.shift_k = (const __nv_bfloat16*)d_in[3]; p.ssm_k = (const __nv_bfloat16*)d_in[4]; p.ssm_D = (const __nv_bfloat16*)d_in[5];
    const __nv_bfloat16* w1 = (const __nv_bfloat16*)d_in[7];
    p.w2 = (const __nv_bfloat16*)d_in[8];
    p.out = (__nv_bfloat16*)d_out;
    void *xn, *w2T, *h, *tT;
    cudaGetSymbolAddress(&xn, g_xn); cudaGetSymbolAddress(&w2T, g_w2T); cudaGetSymbolAddress(&h, g_h); cudaGetSymbolAddress(&tT, g_tT);
    {
        cuuint64_t dims[2] = {640, 2048}, st[1] = {1280}; cuuint32_t box[2] = {64, 128};
        make_map(&p.tm_xn, xn, 2, dims, st, box, true);
    }
    {
        cuuint64_t dims[3] = {64, 640, 24}, st[2] = {3072, 128}; cuuint32_t box[3] = {64, 64, 3};
        make_map(&p.tm_w1, w1, 3, dims, st, box, true);
    }
    {
        cuuint64_t dims[2] = {1536, 2048}, st[1] = {3072}; cuuint32_t box[2] = {64, 64};
        make_map(&p.tm_hst, h, 2, dims, st, box, true);
    }
    {
        cuuint64_t dims[3] = {64, 2048, 24}, st[2] = {3072, 128}; cuuint32_t box[3] = {64, 128, 2};
        make_map(&p.tm_h, h, 3, dims, st, box, true);
    }
    {
        cuuint64_t dims[3] = {64, 640, 24}, st[2] = {3072, 128}; cuuint32_t box[3] = {64, 80, 2};
        make_map(&p.tm_w2T, w2T, 3, dims, st, box, true);
    }
    {
        cuuint64_t dims[2] = {640, 2048}, st[1] = {1280}; cuuint32_t box[2] = {80, 128};
        make_map(&p.tm_xn_e, xn, 2, dims, st, box, false);
        make_map(&p.tm_q_e, p.q, 2, dims, st, box, false);
        cuuint64_t dims2[2] = {2048, 640}, st2[1] = {4096}; cuuint32_t box2[2] = {64, 80};
        make_map(&p.tm_tT_e, tT, 2, dims2, st2, box2, true);
        cuuint32_t box3[2] = {80, 64};
        make_map(&p.tm_out, p.out, 2, dims, st, box3, false);
    }
    cudaFuncSetAttribute(mega_kernel, cudaFuncAttributeMaxDynamicSharedMemorySize, SM_TOTAL);
    mega_kernel<<<NCTA, NTHR, SM_TOTAL>>>(p);
}
```

```cpp
#include <cuda_runtime.h>
#include <cuda_bf16.h>
#include <cuda.h>
#include <stdint.h>

namespace mk {

constexpr int S_LEN = 2048, D_MODEL = 640, D_FF = 1536;
constexpr int NCTA = 128;
constexpr int NTHR = 384;
constexpr int CH_PER_CTA = 5;

__device__ __align__(1024) __nv_bfloat16 g_xn[S_LEN * D_MODEL];
__device__ __align__(1024) __nv_bfloat16 g_kvT[D_MODEL * S_LEN];
__device__ __align__(1024) __nv_bfloat16 g_w2T[D_MODEL * D_FF];
__device__ __align__(1024) __nv_bfloat16 g_h[S_LEN * D_FF];
__device__ __align__(1024) __nv_bfloat16 g_tT[D_MODEL * S_LEN];
constexpr int FL_XN = 0;
constexpr int FL_PREP = 16;
constexpr int FL_H = 17;
constexpr int FL_T = 33;
constexpr int FL_DONE = 41;
constexpr int FL_ERR = 42;
constexpr int FL_W2 = 43;
constexpr int NFLAGS = 44;
__device__ unsigned g_flags[NFLAGS * 32];

#define TSTAMP(i, cond) do {} while (0)
__device__ __forceinline__ uint32_t smem_u32(const void* p) { return (uint32_t)__cvta_generic_to_shared(p); }
__device__ __forceinline__ void mbar_init(uint32_t bar, uint32_t cnt) { asm volatile("mbarrier.init.shared::cta.b64 [%0], %1;" :: "r"(bar), "r"(cnt)); }
__device__ __forceinline__ void mbar_expect_tx(uint32_t bar, uint32_t bytes) { asm volatile("mbarrier.arrive.expect_tx.shared::cta.b64 _, [%0], %1;" :: "r"(bar), "r"(bytes) : "memory"); }
__device__ __forceinline__ void mbar_arrive(uint32_t bar) { asm volatile("mbarrier.arrive.shared::cta.b64 _, [%0];" :: "r"(bar) : "memory"); }
__device__ __forceinline__ void mbar_wait(uint32_t bar, uint32_t parity) {
    uint32_t ok; int it = 0;
    do {
        asm volatile("{\n.reg .pred p;\nmbarrier.try_wait.parity.shared::cta.b64 p, [%1], %2;\nselp.u32 %0, 1, 0, p;\n}\n" : "=r"(ok) : "r"(bar), "r"(parity) : "memory");
        if (++it > (1 << 22)) { g_flags[FL_ERR * 32] = 1; __trap(); }
    } while (!ok);
}
__device__ __forceinline__ void tma_load_2d(uint32_t dst, const CUtensorMap* map, int c0, int c1, uint32_t bar) {
    asm volatile("cp.async.bulk.tensor.2d.shared::cluster.global.mbarrier::complete_tx::bytes [%0], [%1, {%3, %4}], [%2];"
        :: "r"(dst), "l"(map), "r"(bar), "r"(c0), "r"(c1) : "memory");
}
__device__ __forceinline__ void tma_load_3d(uint32_t dst, const CUtensorMap* map, int c0, int c1, int c2, uint32_t bar) {
    asm volatile("cp.async.bulk.tensor.3d.shared::cluster.global.mbarrier::complete_tx::bytes [%0], [%1, {%3, %4, %5}], [%2];"
        :: "r"(dst), "l"(map), "r"(bar), "r"(c0), "r"(c1), "r"(c2) : "memory");
}
__device__ __forceinline__ void tma_store_2d(const CUtensorMap* map, uint32_t src, int c0, int c1) {
    asm volatile("cp.async.bulk.tensor.2d.global.shared::cta.bulk_group [%0, {%2, %3}], [%1];" :: "l"(map), "r"(src), "r"(c0), "r"(c1) : "memory");
}
__device__ __forceinline__ void bulk_commit() { asm volatile("cp.async.bulk.commit_group;" ::: "memory"); }
__device__ __forceinline__ void bulk_wait_all() { asm volatile("cp.async.bulk.wait_group 0;" ::: "memory"); }
__device__ __forceinline__ void fence_proxy_async() { asm volatile("fence.proxy.async;" ::: "memory"); }
__device__ __forceinline__ void fence_proxy_async_smem() { asm volatile("fence.proxy.async.shared::cta;" ::: "memory"); }
__device__ __forceinline__ void named_bar(int id, int n) { asm volatile("bar.sync %0, %1;" :: "r"(id), "r"(n) : "memory"); }
__device__ __forceinline__ void wgmma_fence() { asm volatile("wgmma.fence.sync.aligned;\n" ::: "memory"); }
__device__ __forceinline__ void wgmma_commit() { asm volatile("wgmma.commit_group.sync.aligned;\n" ::: "memory"); }
template<int N> __device__ __forceinline__ void wgmma_wait() { asm volatile("wgmma.wait_group.sync.aligned %0;\n" :: "n"(N) : "memory"); }
__device__ __forceinline__ unsigned ld_acquire(const unsigned* p) { unsigned v; asm volatile("ld.acquire.gpu.global.u32 %0, [%1];" : "=r"(v) : "l"(p) : "memory"); return v; }
__device__ __forceinline__ void wait_flag(int idx, unsigned target) {
    const unsigned* p = &g_flags[idx * 32];
    int it = 0;
    while (ld_acquire(p) < target) { if (++it > (1 << 22)) { g_flags[FL_ERR * 32] = 2; __trap(); } }
}
__device__ __forceinline__ void signal_flag(int idx) {
    __threadfence();
    atomicAdd(&g_flags[idx * 32], 1u);
}
__device__ __forceinline__ float bf2f(__nv_bfloat16 v) { return __bfloat162float(v); }
__device__ __forceinline__ float rbf(float x) { uint32_t r; asm("cvt.rn.bf16x2.f32 %0, %1, %2;" : "=r"(r) : "f"(0.f), "f"(x)); return __uint_as_float(r << 16); }
__device__ __forceinline__ uint32_t pack_bf2(float lo, float hi) { __nv_bfloat162 v = __floats2bfloat162_rn(lo, hi); return *reinterpret_cast<uint32_t*>(&v); }
__device__ __forceinline__ float bflo(uint32_t w) { return __uint_as_float(w << 16); }
__device__ __forceinline__ float bfhi(uint32_t w) { return __uint_as_float(w & 0xffff0000u); }

__device__ __forceinline__ uint32_t bmul2(uint32_t a, uint32_t b) { __nv_bfloat162 r = __hmul2_rn(*reinterpret_cast<__nv_bfloat162*>(&a), *reinterpret_cast<__nv_bfloat162*>(&b)); return *reinterpret_cast<uint32_t*>(&r); }
__device__ __forceinline__ uint32_t badd2(uint32_t a, uint32_t b) { __nv_bfloat162 r = __hadd2_rn(*reinterpret_cast<__nv_bfloat162*>(&a), *reinterpret_cast<__nv_bfloat162*>(&b)); return *reinterpret_cast<uint32_t*>(&r); }
__device__ __forceinline__ uint32_t bsub2(uint32_t a, uint32_t b) { __nv_bfloat162 r = __hsub2_rn(*reinterpret_cast<__nv_bfloat162*>(&a), *reinterpret_cast<__nv_bfloat162*>(&b)); return *reinterpret_cast<uint32_t*>(&r); }
__device__ __forceinline__ float div_by(float a, float d, float r) { float q = a * r; float e = fmaf(-q, d, a); return fmaf(e, r, q); }

__device__ __forceinline__ uint64_t desc_sw128(uint32_t addr, uint32_t lbo_bytes, uint32_t sbo_bytes) {
    return ((uint64_t)((addr & 0x3FFFF) >> 4)) | ((uint64_t)(lbo_bytes >> 4) << 16) | ((uint64_t)(sbo_bytes >> 4) << 32) | ((uint64_t)1 << 62);
}
__device__ __forceinline__ uint64_t desc_nosw(uint32_t addr, uint32_t lbo_bytes, uint32_t sbo_bytes) {
    return ((uint64_t)((addr & 0x3FFFF) >> 4)) | ((uint64_t)(lbo_bytes >> 4) << 16) | ((uint64_t)(sbo_bytes >> 4) << 32);
}

__device__ __forceinline__ void wgmma_rs_n8(float* d, uint32_t a0, uint32_t a1, uint32_t a2, uint32_t a3, uint64_t descB) {
    asm volatile("wgmma.mma_async.sync.aligned.m64n8k16.f32.bf16.bf16 {%0,%1,%2,%3}, {%4,%5,%6,%7}, %8, 1, 1, 1, 0;\n"
        : "+f"(d[0]), "+f"(d[1]), "+f"(d[2]), "+f"(d[3])
        : "r"(a0), "r"(a1), "r"(a2), "r"(a3), "l"(descB));
}
__device__ __forceinline__ void wgmma_rs_n16(float* d, uint32_t a0, uint32_t a1, uint32_t a2, uint32_t a3, uint64_t descB) {
    asm volatile("wgmma.mma_async.sync.aligned.m64n16k16.f32.bf16.bf16 {%0,%1,%2,%3,%4,%5,%6,%7}, {%8,%9,%10,%11}, %12, 1, 1, 1, 0;\n"
        : "+f"(d[0]), "+f"(d[1]), "+f"(d[2]), "+f"(d[3]), "+f"(d[4]), "+f"(d[5]), "+f"(d[6]), "+f"(d[7])
        : "r"(a0), "r"(a1), "r"(a2), "r"(a3), "l"(descB));
}
__device__ __forceinline__ void wgmma_rs_n24(float* d, uint32_t a0, uint32_t a1, uint32_t a2, uint32_t a3, uint64_t descB) {
    asm volatile("wgmma.mma_async.sync.aligned.m64n24k16.f32.bf16.bf16 {%0,%1,%2,%3,%4,%5,%6,%7,%8,%9,%10,%11}, {%12,%13,%14,%15}, %16, 1, 1, 1, 0;\n"
        : "+f"(d[0]), "+f"(d[1]), "+f"(d[2]), "+f"(d[3]), "+f"(d[4]), "+f"(d[5]), "+f"(d[6]), "+f"(d[7]), "+f"(d[8]), "+f"(d[9]), "+f"(d[10]), "+f"(d[11])
        : "r"(a0), "r"(a1), "r"(a2), "r"(a3), "l"(descB));
}
__device__ __forceinline__ void wgmma_rs_n32(float* d, uint32_t a0, uint32_t a1, uint32_t a2, uint32_t a3, uint64_t descB) {
    asm volatile("wgmma.mma_async.sync.aligned.m64n32k16.f32.bf16.bf16 {%0,%1,%2,%3,%4,%5,%6,%7,%8,%9,%10,%11,%12,%13,%14,%15}, {%16,%17,%18,%19}, %20, 1, 1, 1, 0;\n"
        : "+f"(d[0]), "+f"(d[1]), "+f"(d[2]), "+f"(d[3]), "+f"(d[4]), "+f"(d[5]), "+f"(d[6]), "+f"(d[7]), "+f"(d[8]), "+f"(d[9]), "+f"(d[10]), "+f"(d[11]), "+f"(d[12]), "+f"(d[13]), "+f"(d[14]), "+f"(d[15])
        : "r"(a0), "r"(a1), "r"(a2), "r"(a3), "l"(descB));
}
__device__ __forceinline__ void wgmma_rs_n48(float* d, uint32_t a0, uint32_t a1, uint32_t a2, uint32_t a3, uint64_t descB) {
    asm volatile("wgmma.mma_async.sync.aligned.m64n48k16.f32.bf16.bf16 {%0,%1,%2,%3,%4,%5,%6,%7,%8,%9,%10,%11,%12,%13,%14,%15,%16,%17,%18,%19,%20,%21,%22,%23}, {%24,%25,%26,%27}, %28, 1, 1, 1, 0;\n"
        : "+f"(d[0]), "+f"(d[1]), "+f"(d[2]), "+f"(d[3]), "+f"(d[4]), "+f"(d[5]), "+f"(d[6]), "+f"(d[7]), "+f"(d[8]), "+f"(d[9]), "+f"(d[10]), "+f"(d[11]), "+f"(d[12]), "+f"(d[13]), "+f"(d[14]), "+f"(d[15]), "+f"(d[16]), "+f"(d[17]), "+f"(d[18]), "+f"(d[19]), "+f"(d[20]), "+f"(d[21]), "+f"(d[22]), "+f"(d[23])
        : "r"(a0), "r"(a1), "r"(a2), "r"(a3), "l"(descB));
}
__device__ __forceinline__ void wgmma_rs_n64(float* d, uint32_t a0, uint32_t a1, uint32_t a2, uint32_t a3, uint64_t descB) {
    asm volatile("wgmma.mma_async.sync.aligned.m64n64k16.f32.bf16.bf16 {%0,%1,%2,%3,%4,%5,%6,%7,%8,%9,%10,%11,%12,%13,%14,%15,%16,%17,%18,%19,%20,%21,%22,%23,%24,%25,%26,%27,%28,%29,%30,%31}, {%32,%33,%34,%35}, %36, 1, 1, 1, 0;\n"
        : "+f"(d[0]), "+f"(d[1]), "+f"(d[2]), "+f"(d[3]), "+f"(d[4]), "+f"(d[5]), "+f"(d[6]), "+f"(d[7]), "+f"(d[8]), "+f"(d[9]), "+f"(d[10]), "+f"(d[11]), "+f"(d[12]), "+f"(d[13]), "+f"(d[14]), "+f"(d[15]), "+f"(d[16]), "+f"(d[17]), "+f"(d[18]), "+f"(d[19]), "+f"(d[20]), "+f"(d[21]), "+f"(d[22]), "+f"(d[23]), "+f"(d[24]), "+f"(d[25]), "+f"(d[26]), "+f"(d[27]), "+f"(d[28]), "+f"(d[29]), "+f"(d[30]), "+f"(d[31])
        : "r"(a0), "r"(a1), "r"(a2), "r"(a3), "l"(descB));
}
__device__ __forceinline__ void wgmma_ss_n192(float* d, uint64_t descA, uint64_t descB) {
    asm volatile("wgmma.mma_async.sync.aligned.m64n192k16.f32.bf16.bf16 {%0,%1,%2,%3,%4,%5,%6,%7,%8,%9,%10,%11,%12,%13,%14,%15,%16,%17,%18,%19,%20,%21,%22,%23,%24,%25,%26,%27,%28,%29,%30,%31,%32,%33,%34,%35,%36,%37,%38,%39,%40,%41,%42,%43,%44,%45,%46,%47,%48,%49,%50,%51,%52,%53,%54,%55,%56,%57,%58,%59,%60,%61,%62,%63,%64,%65,%66,%67,%68,%69,%70,%71,%72,%73,%74,%75,%76,%77,%78,%79,%80,%81,%82,%83,%84,%85,%86,%87,%88,%89,%90,%91,%92,%93,%94,%95}, %96, %97, 1, 1, 1, 0, 1;\n"
        : "+f"(d[0]), "+f"(d[1]), "+f"(d[2]), "+f"(d[3]), "+f"(d[4]), "+f"(d[5]), "+f"(d[6]), "+f"(d[7]), "+f"(d[8]), "+f"(d[9]), "+f"(d[10]), "+f"(d[11]), "+f"(d[12]), "+f"(d[13]), "+f"(d[14]), "+f"(d[15]), "+f"(d[16]), "+f"(d[17]), "+f"(d[18]), "+f"(d[19]), "+f"(d[20]), "+f"(d[21]), "+f"(d[22]), "+f"(d[23]), "+f"(d[24]), "+f"(d[25]), "+f"(d[26]), "+f"(d[27]), "+f"(d[28]), "+f"(d[29]), "+f"(d[30]), "+f"(d[31]), "+f"(d[32]), "+f"(d[33]), "+f"(d[34]), "+f"(d[35]), "+f"(d[36]), "+f"(d[37]), "+f"(d[38]), "+f"(d[39]), "+f"(d[40]), "+f"(d[41]), "+f"(d[42]), "+f"(d[43]), "+f"(d[44]), "+f"(d[45]), "+f"(d[46]), "+f"(d[47]), "+f"(d[48]), "+f"(d[49]), "+f"(d[50]), "+f"(d[51]), "+f"(d[52]), "+f"(d[53]), "+f"(d[54]), "+f"(d[55]), "+f"(d[56]), "+f"(d[57]), "+f"(d[58]), "+f"(d[59]), "+f"(d[60]), "+f"(d[61]), "+f"(d[62]), "+f"(d[63]), "+f"(d[64]), "+f"(d[65]), "+f"(d[66]), "+f"(d[67]), "+f"(d[68]), "+f"(d[69]), "+f"(d[70]), "+f"(d[71]), "+f"(d[72]), "+f"(d[73]), "+f"(d[74]), "+f"(d[75]), "+f"(d[76]), "+f"(d[77]), "+f"(d[78]), "+f"(d[79]), "+f"(d[80]), "+f"(d[81]), "+f"(d[82]), "+f"(d[83]), "+f"(d[84]), "+f"(d[85]), "+f"(d[86]), "+f"(d[87]), "+f"(d[88]), "+f"(d[89]), "+f"(d[90]), "+f"(d[91]), "+f"(d[92]), "+f"(d[93]), "+f"(d[94]), "+f"(d[95])
        : "l"(descA), "l"(descB));
}
__device__ __forceinline__ void wgmma_ss_n80(float* d, uint64_t descA, uint64_t descB) {
    asm volatile("wgmma.mma_async.sync.aligned.m64n80k16.f32.bf16.bf16 {%0,%1,%2,%3,%4,%5,%6,%7,%8,%9,%10,%11,%12,%13,%14,%15,%16,%17,%18,%19,%20,%21,%22,%23,%24,%25,%26,%27,%28,%29,%30,%31,%32,%33,%34,%35,%36,%37,%38,%39}, %40, %41, 1, 1, 1, 0, 0;\n"
        : "+f"(d[0]), "+f"(d[1]), "+f"(d[2]), "+f"(d[3]), "+f"(d[4]), "+f"(d[5]), "+f"(d[6]), "+f"(d[7]), "+f"(d[8]), "+f"(d[9]), "+f"(d[10]), "+f"(d[11]), "+f"(d[12]), "+f"(d[13]), "+f"(d[14]), "+f"(d[15]), "+f"(d[16]), "+f"(d[17]), "+f"(d[18]), "+f"(d[19]), "+f"(d[20]), "+f"(d[21]), "+f"(d[22]), "+f"(d[23]), "+f"(d[24]), "+f"(d[25]), "+f"(d[26]), "+f"(d[27]), "+f"(d[28]), "+f"(d[29]), "+f"(d[30]), "+f"(d[31]), "+f"(d[32]), "+f"(d[33]), "+f"(d[34]), "+f"(d[35]), "+f"(d[36]), "+f"(d[37]), "+f"(d[38]), "+f"(d[39])
        : "l"(descA), "l"(descB));
}
__device__ __forceinline__ void wgmma_ss_n64(float* d, uint64_t descA, uint64_t descB) {
    asm volatile("wgmma.mma_async.sync.aligned.m64n64k16.f32.bf16.bf16 {%0,%1,%2,%3,%4,%5,%6,%7,%8,%9,%10,%11,%12,%13,%14,%15,%16,%17,%18,%19,%20,%21,%22,%23,%24,%25,%26,%27,%28,%29,%30,%31}, %32, %33, 1, 1, 1, 0, 0;\n"
        : "+f"(d[0]), "+f"(d[1]), "+f"(d[2]), "+f"(d[3]), "+f"(d[4]), "+f"(d[5]), "+f"(d[6]), "+f"(d[7]), "+f"(d[8]), "+f"(d[9]), "+f"(d[10]), "+f"(d[11]), "+f"(d[12]), "+f"(d[13]), "+f"(d[14]), "+f"(d[15]), "+f"(d[16]), "+f"(d[17]), "+f"(d[18]), "+f"(d[19]), "+f"(d[20]), "+f"(d[21]), "+f"(d[22]), "+f"(d[23]), "+f"(d[24]), "+f"(d[25]), "+f"(d[26]), "+f"(d[27]), "+f"(d[28]), "+f"(d[29]), "+f"(d[30]), "+f"(d[31])
        : "l"(descA), "l"(descB));
}
__device__ __forceinline__ void wgmma_ss_n48(float* d, uint64_t descA, uint64_t descB) {
    asm volatile("wgmma.mma_async.sync.aligned.m64n48k16.f32.bf16.bf16 {%0,%1,%2,%3,%4,%5,%6,%7,%8,%9,%10,%11,%12,%13,%14,%15,%16,%17,%18,%19,%20,%21,%22,%23}, %24, %25, 1, 1, 1, 0, 0;\n"
        : "+f"(d[0]), "+f"(d[1]), "+f"(d[2]), "+f"(d[3]), "+f"(d[4]), "+f"(d[5]), "+f"(d[6]), "+f"(d[7]), "+f"(d[8]), "+f"(d[9]), "+f"(d[10]), "+f"(d[11]), "+f"(d[12]), "+f"(d[13]), "+f"(d[14]), "+f"(d[15]), "+f"(d[16]), "+f"(d[17]), "+f"(d[18]), "+f"(d[19]), "+f"(d[20]), "+f"(d[21]), "+f"(d[22]), "+f"(d[23])
        : "l"(descA), "l"(descB));
}
__device__ __forceinline__ void wgmma_ss_n32(float* d, uint64_t descA, uint64_t descB) {
    asm volatile("wgmma.mma_async.sync.aligned.m64n32k16.f32.bf16.bf16 {%0,%1,%2,%3,%4,%5,%6,%7,%8,%9,%10,%11,%12,%13,%14,%15}, %16, %17, 1, 1, 1, 0, 0;\n"
        : "+f"(d[0]), "+f"(d[1]), "+f"(d[2]), "+f"(d[3]), "+f"(d[4]), "+f"(d[5]), "+f"(d[6]), "+f"(d[7]), "+f"(d[8]), "+f"(d[9]), "+f"(d[10]), "+f"(d[11]), "+f"(d[12]), "+f"(d[13]), "+f"(d[14]), "+f"(d[15])
        : "l"(descA), "l"(descB));
}
__device__ __forceinline__ void wgmma_ss_n16(float* d, uint64_t descA, uint64_t descB) {
    asm volatile("wgmma.mma_async.sync.aligned.m64n16k16.f32.bf16.bf16 {%0,%1,%2,%3,%4,%5,%6,%7}, %8, %9, 1, 1, 1, 0, 0;\n"
        : "+f"(d[0]), "+f"(d[1]), "+f"(d[2]), "+f"(d[3]), "+f"(d[4]), "+f"(d[5]), "+f"(d[6]), "+f"(d[7])
        : "l"(descA), "l"(descB));
}

constexpr int SM_PIPE = 0;
constexpr int ST1_BYTES = 40960, ST1_N = 4;
constexpr int ST2_BYTES = 53248, ST2_N = 3;
constexpr int SM_CU = 2 * ST2_BYTES;
constexpr int SM_CT = SM_CU + 2 * 18432;
constexpr int SM_X = 163840;
constexpr int SM_U = SM_X;
constexpr int F_COPY1 = 4224 + 64;
constexpr int F_BYTES = F_COPY1 + 4224;
constexpr int SM_F = SM_X + 2 * 13824;
constexpr int SM_BAR = SM_F + 2 * F_BYTES;
constexpr int SM_TOTAL = SM_BAR + 256;
constexpr int B_FULL1 = 0, B_EMPTY1 = 4, B_FULL2 = 8, B_EMPTY2 = 11, B_G1DONE = 14, B_CONVDONE = 15, B_HSTG = 16, B_W2DONE = 18;

struct Params {
    CUtensorMap tm_xn, tm_w1, tm_hst, tm_h, tm_w2T, tm_xn_e, tm_q_e, tm_tT_e, tm_out;
    const __nv_bfloat16 *q, *k, *v, *shift_k, *ssm_k, *ssm_D, *w2;
    __nv_bfloat16* out;
};

#define SKIP_KV 0
#define SKIP_KVST 0
#define SKIP_W2 0
__device__ __forceinline__ void prep_w2T(const Params& p, uint8_t* smem, int cta, uint32_t bar_w2done) {
    const int lane = threadIdx.x & 31;
        const int k0 = (cta >> 3) * 96, n0 = (cta & 7) * 80;
        uint8_t* stg = smem + SM_U;
        #pragma unroll 1
        for (int bt = 0; bt < (SKIP_W2 ? 0 : 3); bt++) {
            uint4 vv[10];
            #pragma unroll
            for (int it = 0; it < 10; it++) {
                const int idx = lane + 32 * (bt * 10 + it);
                const int r = idx / 10, c = idx % 10;
                vv[it] = *reinterpret_cast<const uint4*>(p.w2 + (size_t)(k0 + r) * D_MODEL + n0 + c * 8);
            }
            #pragma unroll
            for (int it = 0; it < 10; it++) {
                const int idx = lane + 32 * (bt * 10 + it);
                const int r = idx / 10, c = idx % 10;
                uint32_t w[4] = {vv[it].x, vv[it].y, vv[it].z, vv[it].w};
                #pragma unroll
                for (int e = 0; e < 4; e++) {
                    *reinterpret_cast<uint16_t*>(stg + (c * 8 + 2 * e) * 208 + r * 2) = (uint16_t)(w[e] & 0xffffu);
                    *reinterpret_cast<uint16_t*>(stg + (c * 8 + 2 * e + 1) * 208 + r * 2) = (uint16_t)(w[e] >> 16);
                }
            }
        }
        __syncwarp();
        #pragma unroll 1
        for (int bt = 0; bt < (SKIP_W2 ? 0 : 3); bt++) {
            #pragma unroll
            for (int it = 0; it < 10; it++) {
                const int idx = lane + 32 * (bt * 10 + it);
                const int n = idx / 12, c = idx % 12;
                uint4 v4 = *reinterpret_cast<const uint4*>(stg + n * 208 + c * 16);
                *reinterpret_cast<uint4*>(g_w2T + (size_t)(n0 + n) * D_FF + k0 + c * 8) = v4;
            }
        }
        __syncwarp();
        if (lane == 0) { mbar_arrive(bar_w2done); __threadfence(); atomicAdd(&g_flags[FL_W2 * 32], 1u); }
}
__device__ __forceinline__ void prep_phase(const Params& p, uint8_t* smem, int cta) {
    const int tid = threadIdx.x, warp = tid >> 5, lane = tid & 31;
    const int s0 = cta * 16;
    if (warp < 8) {
        uint32_t w[2][10];
        #pragma unroll
        for (int rr = 0; rr < 2; rr++) {
            const __nv_bfloat16* xr = p.q + (size_t)(s0 + warp * 2 + rr) * D_MODEL;
            uint4 a = *reinterpret_cast<const uint4*>(xr + lane * 8);
            uint4 b = *reinterpret_cast<const uint4*>(xr + 256 + lane * 8);
            uint2 c = *reinterpret_cast<const uint2*>(xr + 512 + lane * 4);
            w[rr][0] = a.x; w[rr][1] = a.y; w[rr][2] = a.z; w[rr][3] = a.w; w[rr][4] = b.x; w[rr][5] = b.y; w[rr][6] = b.z; w[rr][7] = b.w; w[rr][8] = c.x; w[rr][9] = c.y;
        }
        #pragma unroll 1
        for (int rr = 0; rr < 2; rr++) {
            uint32_t wr[10];
            #pragma unroll
            for (int i = 0; i < 10; i++) wr[i] = rr ? w[1][i] : w[0][i];
            float x[20];
            #pragma unroll
            for (int i = 0; i < 10; i++) { x[2 * i] = bflo(wr[i]); x[2 * i + 1] = bfhi(wr[i]); }
            float sum = 0.f;
            #pragma unroll
            for (int i = 0; i < 20; i++) sum += x[i];
            #pragma unroll
            for (int o = 16; o > 0; o >>= 1) sum += __shfl_xor_sync(0xffffffffu, sum, o);
            const float mean = sum * (1.0f / 640.0f);
            float sq = 0.f;
            #pragma unroll
            for (int i = 0; i < 20; i++) { float dd = x[i] - mean; sq += dd * dd; }
            #pragma unroll
            for (int o = 16; o > 0; o >>= 1) sq += __shfl_xor_sync(0xffffffffu, sq, o);
            const float var_b = rbf(sq * (1.0f / 640.0f));
            const uint32_t m2 = pack_bf2(mean, mean);
            const float den = rbf(__fsqrt_rn(rbf(var_b + 1e-5f)));
            const float rden = __frcp_rn(den);
            uint32_t o[10];
            #pragma unroll
            for (int i = 0; i < 10; i++) {
                const uint32_t c2 = bsub2(wr[i], m2);
                o[i] = pack_bf2(div_by(bflo(c2), den, rden), div_by(bfhi(c2), den, rden));
            }
            __nv_bfloat16* yr = g_xn + (size_t)(s0 + warp * 2 + rr) * D_MODEL;
            *reinterpret_cast<uint4*>(yr + lane * 8) = make_uint4(o[0], o[1], o[2], o[3]);
            *reinterpret_cast<uint4*>(yr + 256 + lane * 8) = make_uint4(o[4], o[5], o[6], o[7]);
            *reinterpret_cast<uint2*>(yr + 512 + lane * 4) = make_uint2(o[8], o[9]);
        }
        named_bar(1, 256);
        if (tid == 0) { __threadfence(); atomicAdd(&g_flags[(FL_XN + (cta >> 3)) * 32], 1u); }
        __syncwarp();
        asm volatile("bar.arrive 5, 384;" ::: "memory");
    } else {
        const int t = tid - 256;
        const int half = t & 1;
        uint32_t kw[5][11], vw[5][8]; uint4 sk[5];
        #pragma unroll
        for (int it = 0; it < 5; it++) {
            const int d = 2 * ((t >> 1) + 64 * it);
            const int r0 = s0 + 8 * half;
            sk[it] = *reinterpret_cast<const uint4*>(p.shift_k + d * 4);
            #pragma unroll
            for (int j = 0; j < 11; j++) {
                const int row = r0 - 3 + j;
                kw[it][j] = (row >= 0) ? *reinterpret_cast<const uint32_t*>(p.k + (size_t)row * D_MODEL + d) : 0u;
            }
            #pragma unroll
            for (int j = 0; j < 8; j++) vw[it][j] = *reinterpret_cast<const uint32_t*>(p.v + (size_t)(r0 + j) * D_MODEL + d);
        }
        uint32_t o0[5][4], o1[5][4];
        #pragma unroll
        for (int it = 0; it < 5; it++) {
            const uint32_t W0 = __byte_perm(sk[it].x, sk[it].z, 0x5410), W1 = __byte_perm(sk[it].x, sk[it].z, 0x7632);
            const uint32_t W2 = __byte_perm(sk[it].y, sk[it].w, 0x5410), W3 = __byte_perm(sk[it].y, sk[it].w, 0x7632);
            uint32_t r[8];
            #pragma unroll
            for (int j = 0; j < 8; j++) {
                uint32_t a = bmul2(kw[it][j], W3);
                a = badd2(a, bmul2(kw[it][j + 1], W2));
                a = badd2(a, bmul2(kw[it][j + 2], W1));
                a = badd2(a, bmul2(kw[it][j + 3], W0));
                r[j] = bmul2(a, vw[it][j]);
            }
            #pragma unroll
            for (int j = 0; j < 4; j++) { o0[it][j] = __byte_perm(r[2 * j], r[2 * j + 1], 0x5410); o1[it][j] = __byte_perm(r[2 * j], r[2 * j + 1], 0x7632); }
        }
        named_bar(5, 384);
        #pragma unroll
        for (int it = 0; it < 5; it++) {
            const int d = 2 * ((t >> 1) + 64 * it);
            *reinterpret_cast<uint4*>(g_kvT + (size_t)d * S_LEN + s0 + 8 * half) = make_uint4(o0[it][0], o0[it][1], o0[it][2], o0[it][3]);
            *reinterpret_cast<uint4*>(g_kvT + (size_t)(d + 1) * S_LEN + s0 + 8 * half) = make_uint4(o1[it][0], o1[it][1], o1[it][2], o1[it][3]);
        }
        named_bar(3, 128);
        if (t == 0) { __threadfence(); atomicAdd(&g_flags[FL_PREP * 32], 1u); }
    }
}

__device__ __forceinline__ void stmatrix_x4(uint32_t addr, uint32_t r0, uint32_t r1, uint32_t r2, uint32_t r3) {
    asm volatile("stmatrix.sync.aligned.m8n8.x4.shared.b16 [%0], {%1, %2, %3, %4};" :: "r"(addr), "r"(r0), "r"(r1), "r"(r2), "r"(r3) : "memory");
}
__device__ __forceinline__ uint32_t lds32(uint32_t addr) { uint32_t v; asm volatile("ld.shared.u32 %0, [%1];" : "=r"(v) : "r"(addr)); return v; }

constexpr int UST = 1152;
constexpr int UCOPY = 4 * UST;
constexpr int UBUF = 4 * UCOPY;
template<int E>
__device__ __forceinline__ void conv_mma2(float* acc, const uint32_t (&A)[8], uint64_t descB) {
    #pragma unroll
    for (int kk = 0; kk < 2; kk++) {
        const uint64_t db = descB + (uint64_t)((2 * kk * UST) >> 4);
        if (E == 0) wgmma_rs_n64(acc, A[4 * kk], A[4 * kk + 1], A[4 * kk + 2], A[4 * kk + 3], db);
        if (E == 1) wgmma_rs_n48(acc, A[4 * kk], A[4 * kk + 1], A[4 * kk + 2], A[4 * kk + 3], db);
        if (E == 2) wgmma_rs_n32(acc, A[4 * kk], A[4 * kk + 1], A[4 * kk + 2], A[4 * kk + 3], db);
        if (E == 3) wgmma_rs_n16(acc, A[4 * kk], A[4 * kk + 1], A[4 * kk + 2], A[4 * kk + 3], db);
    }
}
__device__ __forceinline__ uint32_t swap16(uint32_t x) { uint32_t r; asm volatile("prmt.b32 %0, %1, 0, 0x1032;" : "=r"(r) : "r"(x)); return r; }
__device__ __forceinline__ void conv_ldP(uint32_t (&P)[5], uint32_t pfa, int s) {
    #pragma unroll
    for (int j = 0; j < 5; j++) P[j] = lds32(pfa + s * 128 + j * 16);
}
__device__ __forceinline__ void conv_mkA(uint32_t (&A)[8], const uint32_t (&P)[5]) {
    A[0] = swap16(P[3]); A[1] = swap16(P[4]); A[2] = swap16(P[2]); A[3] = swap16(P[3]);
    A[4] = swap16(P[1]); A[5] = swap16(P[2]); A[6] = swap16(P[0]); A[7] = swap16(P[1]);
}
__host__ __device__ constexpr int conv_step_of(int i) { return 8 * (i & 3) + (i >> 2); }
template<int I> struct ConvStep {
    __device__ static __forceinline__ void run(float* acc0, float* acc1, float* acc2, float* acc3, uint32_t (&A)[3][8], uint32_t (&P)[5], uint32_t pfa, uint32_t ubs) {
        if (I + 1 < 32) conv_mkA(A[(I + 1) % 3], P);
        if (I + 2 < 32) conv_ldP(P, pfa, conv_step_of(I + 2));
        constexpr int r = I >> 2;
        const uint64_t db = desc_nosw(ubs + (r & 3) * UCOPY + ((r >> 2) ? 0 : 128), UST, 128);
        wgmma_fence();
        if ((I & 3) == 0) conv_mma2<0>(acc0, A[I % 3], db);
        if ((I & 3) == 1) conv_mma2<1>(acc1, A[I % 3], db);
        if ((I & 3) == 2) conv_mma2<2>(acc2, A[I % 3], db);
        if ((I & 3) == 3) conv_mma2<3>(acc3, A[I % 3], db);
        wgmma_commit();
        wgmma_wait<1>();
        ConvStep<I + 1>::run(acc0, acc1, acc2, acc3, A, P, pfa, ubs);
    }
};
template<> struct ConvStep<32> { __device__ static __forceinline__ void run(float*, float*, float*, float*, uint32_t (&)[3][8], uint32_t (&)[5], uint32_t, uint32_t) {} };

#define EARLY_B 0
__global__ void __launch_bounds__(NTHR, 1) mega_kernel(const __grid_constant__ Params p) {
    extern __shared__ __align__(1024) uint8_t smem[];
    const int tid = threadIdx.x, warp = tid >> 5, lane = tid & 31;
    const int cta = blockIdx.x;
    const int tb = cta >> 3, ns = cta & 7;
    const uint32_t sbase = smem_u32(smem);
    const uint32_t bar0 = sbase + SM_BAR;
    #define BAR(i) (bar0 + (i) * 8)
    TSTAMP(15, tid == 0);

    if (tid == 0) {
        for (int i = 0; i < ST1_N; i++) { mbar_init(BAR(B_FULL1 + i), 1); mbar_init(BAR(B_EMPTY1 + i), 2); }
        for (int i = 0; i < ST2_N; i++) { mbar_init(BAR(B_FULL2 + i), 1); mbar_init(BAR(B_EMPTY2 + i), 2); }
        mbar_init(BAR(B_G1DONE), 1); mbar_init(BAR(B_CONVDONE), 2); mbar_init(BAR(B_HSTG), 1); mbar_init(BAR(B_W2DONE), 1); mbar_init(BAR(B_HSTG + 1), 1);
        asm volatile("fence.mbarrier_init.release.cluster;" ::: "memory");
    }
    __syncthreads();
    if (warp == 8) {
        const void* ptr = nullptr;
        switch (lane) {
            case 0: ptr = g_xn + (size_t)cta * 16 * D_MODEL; break;
            case 1: ptr = g_kvT + (size_t)cta * CH_PER_CTA * S_LEN; break;
            case 2: ptr = g_h + (size_t)(tb * 128) * D_FF + ns * 192; break;
            case 3: ptr = g_tT + (size_t)cta * CH_PER_CTA * S_LEN; break;
            case 4: ptr = g_w2T + (size_t)(ns * 80) * D_FF; break;
            case 5: ptr = g_flags; break;
            case 6: ptr = p.out + (size_t)(tb * 128) * D_MODEL; break;
            case 7: ptr = p.ssm_k + (size_t)cta * CH_PER_CTA * S_LEN; break;
            case 8: ptr = p.ssm_D; break;
            case 9: ptr = p.w2; break;
            default: break;
        }
        if (ptr) { uint32_t dummy; asm volatile("ld.global.u32 %0, [%1];" : "=r"(dummy) : "l"(ptr)); }
    }
    if (EARLY_B && warp == 8 && lane == 0) {
        for (int kb = 0; kb < ST1_N; kb++) {
            mbar_expect_tx(BAR(B_FULL1 + kb), ST1_BYTES);
            tma_load_3d(sbase + SM_PIPE + kb * ST1_BYTES + 16384, &p.tm_w1, 0, kb * 64, ns * 3, BAR(B_FULL1 + kb));
        }
    }
    prep_phase(p, smem, cta);
    if (warp == 9) prep_w2T(p, smem, cta, BAR(B_W2DONE));
    TSTAMP(0, tid == 0);

    if (warp >= 8) {
        if (warp == 9 && lane == 0) {
            #pragma unroll
            for (int hf = 0; hf < 2; hf++) {
                mbar_wait(BAR(B_HSTG + hf), 0);
                #pragma unroll
                for (int nb = 0; nb < 3; nb++)
                    tma_store_2d(&p.tm_hst, sbase + SM_PIPE + nb * 16384 + hf * 8192, ns * 192 + nb * 64, tb * 128 + hf * 64);
                bulk_commit();
            }
            bulk_wait_all();
            mbar_arrive(BAR(B_G1DONE));
            __threadfence();
            atomicAdd(&g_flags[(FL_H + tb) * 32], 2u);
        }
        if (warp == 8 && lane == 0) {
            for (int kb = ST1_N; kb < 10; kb++) {
                const int s = kb % ST1_N;
                if (kb >= ST1_N) mbar_wait(BAR(B_EMPTY1 + s), ((kb / ST1_N) - 1) & 1);
                const uint32_t st = sbase + SM_PIPE + s * ST1_BYTES;
                if (!EARLY_B || kb >= ST1_N) mbar_expect_tx(BAR(B_FULL1 + s), ST1_BYTES);
                tma_load_2d(st, &p.tm_xn, kb * 64, tb * 128, BAR(B_FULL1 + s));
                if (!EARLY_B || kb >= ST1_N) tma_load_3d(st + 16384, &p.tm_w1, 0, kb * 64, ns * 3, BAR(B_FULL1 + s));
            }
            mbar_wait(BAR(B_G1DONE), 0);
            wait_flag(FL_W2, NCTA);
            wait_flag(FL_H + tb, 16);
            fence_proxy_async();
            for (int it = 0; it < 12; it++) {
                const int s = it % ST2_N;
                if (it >= ST2_N) mbar_wait(BAR(B_EMPTY2 + s), ((it / ST2_N) - 1) & 1);
                if (it == 2) mbar_wait(BAR(B_CONVDONE), 0);
                const uint32_t st = sbase + SM_PIPE + s * ST2_BYTES;
                mbar_expect_tx(BAR(B_FULL2 + s), ST2_BYTES);
                tma_load_3d(st, &p.tm_h, 0, tb * 128, it * 2, BAR(B_FULL2 + s));
                tma_load_3d(st + 32768, &p.tm_w2T, 0, ns * 80, it * 2, BAR(B_FULL2 + s));
            }
            mbar_wait(BAR(B_EMPTY2 + 0), ((12 / ST2_N) - 1) & 1);
            mbar_expect_tx(BAR(B_FULL2 + 0), 2 * 20480);
            tma_load_2d(sbase + SM_PIPE, &p.tm_xn_e, ns * 80, tb * 128, BAR(B_FULL2 + 0));
            tma_load_2d(sbase + SM_PIPE + 20480, &p.tm_q_e, ns * 80, tb * 128, BAR(B_FULL2 + 0));
            mbar_wait(BAR(B_EMPTY2 + 1), ((13 / ST2_N) - 1) & 1);
            wait_flag(FL_T + ns, 16);
            fence_proxy_async();
            mbar_expect_tx(BAR(B_FULL2 + 1), 20480);
            tma_load_2d(sbase + SM_PIPE + ST2_BYTES, &p.tm_tT_e, tb * 128, ns * 80, BAR(B_FULL2 + 1));
            tma_load_2d(sbase + SM_PIPE + ST2_BYTES + 10240, &p.tm_tT_e, tb * 128 + 64, ns * 80, BAR(B_FULL2 + 1));
        }
    } else {
        const int wg = warp >> 2;
        const int w = warp & 3;
        const int wt = tid & 127;
        const int g = lane >> 2, q = lane & 3;
        if (tid == 0) {
            wait_flag(FL_XN + tb, 8);
            fence_proxy_async();
            for (int kb = 0; kb < ST1_N; kb++) {
                const uint32_t st = sbase + SM_PIPE + kb * ST1_BYTES;
                mbar_expect_tx(BAR(B_FULL1 + kb), ST1_BYTES);
                tma_load_2d(st, &p.tm_xn, kb * 64, tb * 128, BAR(B_FULL1 + kb));
                tma_load_3d(st + 16384, &p.tm_w1, 0, kb * 64, ns * 3, BAR(B_FULL1 + kb));
            }
        }
        __syncwarp();
        {
            float acc[96];
            #pragma unroll
            for (int i = 0; i < 96; i++) acc[i] = 0.f;
            for (int kb = 0; kb < 10; kb++) {
                const int s = kb % ST1_N;
                mbar_wait(BAR(B_FULL1 + s), (kb / ST1_N) & 1);
                if (kb == 0) TSTAMP(10, tid == 0);
                const uint32_t sa = sbase + SM_PIPE + s * ST1_BYTES + wg * 8192;
                const uint32_t sb = sbase + SM_PIPE + s * ST1_BYTES + 16384;
                wgmma_fence();
                #pragma unroll
                for (int kk = 0; kk < 4; kk++)
                    wgmma_ss_n192(acc, desc_sw128(sa + kk * 32, 16, 1024), desc_sw128(sb + kk * 2048, 8192, 1024));
                wgmma_commit();
                wgmma_wait<0>();
                if (wt == 0) mbar_arrive(BAR(B_EMPTY1 + s));
            }
            TSTAMP(1, tid == 0);
            named_bar(1, 256);
            const uint32_t stg = sbase + SM_PIPE;
            const int m = lane >> 3, r = lane & 7;
            const int row = 16 * w + (m & 1) * 8 + r;
            #pragma unroll
            for (int j2 = 0; j2 < 12; j2++) {
                const int nb = j2 >> 2, cb = (2 * j2) & 7;
                uint32_t r0 = pack_bf2(fmaxf(acc[8 * j2 + 0], 0.f), fmaxf(acc[8 * j2 + 1], 0.f));
                uint32_t r1 = pack_bf2(fmaxf(acc[8 * j2 + 2], 0.f), fmaxf(acc[8 * j2 + 3], 0.f));
                uint32_t r2 = pack_bf2(fmaxf(acc[8 * j2 + 4], 0.f), fmaxf(acc[8 * j2 + 5], 0.f));
                uint32_t r3 = pack_bf2(fmaxf(acc[8 * j2 + 6], 0.f), fmaxf(acc[8 * j2 + 7], 0.f));
                const int chunk = cb + (m >> 1);
                stmatrix_x4(stg + nb * 16384 + wg * 8192 + row * 128 + ((chunk ^ (row & 7)) << 4), r0, r1, r2, r3);
            }
            fence_proxy_async_smem();
            named_bar(2 + wg, 128);
            if (wt == 0) mbar_arrive(BAR(B_HSTG + wg));
        }
        TSTAMP(2, tid == 0);
        {
            uint8_t* ub = smem + SM_CU + wg * UBUF;
            uint8_t* fb = smem + SM_F + wg * F_BYTES;
            float* X = reinterpret_cast<float*>(smem + SM_X + wg * 13824);
            uint8_t* Tst = smem + SM_CT + wg * 4096;
            named_bar(1, 256);
            for (int i = wt; i < 4 * 4 * 16; i += 128) {
                const int rho = i >> 6, st = (i >> 4) & 3, rr = i & 15;
                if (rr < 8 + 2 * rho) *reinterpret_cast<uint4*>(ub + rho * UCOPY + st * UST + rr * 16) = make_uint4(0, 0, 0, 0);
            }
            if (wt < 16) {
                const int cp = (wt >> 3) & 1, rr = wt & 7;
                *reinterpret_cast<uint4*>(fb + cp * F_COPY1 + rr * 16) = make_uint4(0, 0, 0, 0);
            }
            if (wt == 0) { wait_flag(FL_PREP, NCTA); mbar_wait(BAR(B_W2DONE), 0); }
            named_bar(2 + wg, 128);
            TSTAMP(3, tid == 0);
            const int d0 = cta * CH_PER_CTA;
            const int nch = (wg == 0) ? 3 : 2;
            uint4 pu[2], pf[2]; uint32_t pprev[2]; __nv_bfloat16 pD;
            auto gload = [&](int d) {
                pD = p.ssm_D[d];
                #pragma unroll
                for (int j = 0; j < 2; j++) {
                    const int idx = wt + 128 * j;
                    pu[j] = *reinterpret_cast<const uint4*>(g_kvT + (size_t)d * S_LEN + (idx & 63) * 32 + (idx >> 6) * 8);
                    pf[j] = *reinterpret_cast<const uint4*>(p.ssm_k + (size_t)d * S_LEN + idx * 8);
                    pprev[j] = (idx > 0) ? (uint32_t)*reinterpret_cast<const uint16_t*>(p.ssm_k + (size_t)d * S_LEN + idx * 8 - 1) : 0u;
                }
            };
            gload(d0 + wg);
            if (wg == 1) asm volatile("bar.arrive 6, 256;" ::: "memory");
            const uint32_t pf_off = (g & 1) ? (128 + 2 * (g - 1 - 2 * q)) : (F_COPY1 + 128 + 2 * (g - 2 * q));
            const uint32_t pfa = smem_u32(fb) + pf_off + 32 * w - 3 * 16;
            const uint32_t ubs = smem_u32(ub);
            for (int ci = 0; ci < nch; ci++) {
                const int d = d0 + 2 * ci + wg;
                #pragma unroll
                for (int j = 0; j < 2; j++) {
                    const int idx = wt + 128 * j;
                    const int a = idx & 63, kg = idx >> 6;
                    #pragma unroll
                    for (int rho = 0; rho < 4; rho++)
                        if (a + 8 + 2 * rho < 72) *reinterpret_cast<uint4*>(ub + rho * UCOPY + kg * UST + (a + 8 + 2 * rho) * 16) = pu[j];
                    *reinterpret_cast<uint4*>(fb + 128 + idx * 16) = pf[j];
                    *reinterpret_cast<uint4*>(fb + F_COPY1 + 128 + idx * 16) =
                        make_uint4(__byte_perm(pprev[j], pf[j].x, 0x5410), __byte_perm(pf[j].x, pf[j].y, 0x5432), __byte_perm(pf[j].y, pf[j].z, 0x5432), __byte_perm(pf[j].z, pf[j].w, 0x5432));
                }
                const float Dd = bf2f(pD);
                fence_proxy_async_smem();
                named_bar(2 + wg, 128);
                if (ci + 1 < nch) gload(d + 2);

                float acc0[32], acc1[24], acc2[16], acc3[8];
                #pragma unroll
                for (int i = 0; i < 32; i++) acc0[i] = 0.f;
                #pragma unroll
                for (int i = 0; i < 24; i++) acc1[i] = 0.f;
                #pragma unroll
                for (int i = 0; i < 16; i++) acc2[i] = 0.f;
                #pragma unroll
                for (int i = 0; i < 8; i++) acc3[i] = 0.f;
                named_bar(6 + wg, 256);

                {
                    uint32_t A[3][8], P[5];
                    conv_ldP(P, pfa, conv_step_of(0)); conv_mkA(A[0], P); conv_ldP(P, pfa, conv_step_of(1));
                    ConvStep<0>::run(acc0, acc1, acc2, acc3, A, P, pfa, ubs);
                    wgmma_wait<0>();
                }
                if (!(wg == 0 && ci == 2)) asm volatile("bar.arrive %0, 256;" :: "r"(7 - wg) : "memory");
                #pragma unroll
                for (int i = 0; i < 32; i++) {
                    float v = acc0[i];
                    if (i >= 8) v += acc1[i - 8];
                    if (i >= 16) v += acc2[i - 16];
                    if (i >= 24) v += acc3[i - 24];
                    acc0[i] = v;
                }

                const int bl = 16 * (w & 1) + g;
                float* X1 = X;
                float* X0 = X + 64 * 36;
                if (w >= 2) {
                    #pragma unroll
                    for (int i = 0; i < 32; i++) { const int col = 8 * (i >> 2) + 2 * q + (i & 1); if (col < 63) X1[(col + 1) * 36 + bl + ((i >> 1) & 1) * 8] = acc0[i]; }
                } else {
                    #pragma unroll
                    for (int i = 16; i < 32; i++) X0[(8 * (i >> 2) + 2 * q + (i & 1) - 32) * 36 + bl + ((i >> 1) & 1) * 8] = acc0[i];
                }

                named_bar(2 + wg, 128);

                __nv_bfloat16* T = reinterpret_cast<__nv_bfloat16*>(Tst);
                float yv[16], uv[16];
                #pragma unroll
                for (int i = 0; i < 16; i++) {
                    const int b = bl + ((i >> 1) & 1) * 8;
                    const int a = 8 * (i >> 2) + 2 * q + (i & 1) + ((w < 2) ? 0 : 32);
                    if (w < 2) yv[i] = acc0[i] + ((a > 0) ? X1[a * 36 + b] : 0.f);
                    else yv[i] = X0[(a - 32) * 36 + b] + X1[a * 36 + b];
                    uv[i] = bf2f(*reinterpret_cast<const __nv_bfloat16*>(ub + (b >> 3) * UST + (a + 8) * 16 + (b & 7) * 2));
                }
                #pragma unroll
                for (int i = 0; i < 16; i++) {
                    const int b = bl + ((i >> 1) & 1) * 8;
                    const int a = 8 * (i >> 2) + 2 * q + (i & 1) + ((w < 2) ? 0 : 32);
                    T[32 * a + b] = __float2bfloat16_rn(rbf(yv[i]) + rbf(uv[i] * Dd));
                }

                named_bar(2 + wg, 128);

                #pragma unroll
                for (int j = 0; j < 2; j++)
                    *reinterpret_cast<uint4*>(g_tT + (size_t)d * S_LEN + (wt + 128 * j) * 8) = *reinterpret_cast<const uint4*>(Tst + (wt + 128 * j) * 16);

            }
            named_bar(1, 256);
            if (wt == 0) mbar_arrive(BAR(B_CONVDONE));
            if (tid == 0) signal_flag(FL_T + (cta >> 4));
        }
        TSTAMP(4, tid == 0);
        {
            float acc[40];
            #pragma unroll
            for (int i = 0; i < 40; i++) acc[i] = 0.f;
            for (int it = 0; it < 12; it++) {
                const int s = it % ST2_N;
                mbar_wait(BAR(B_FULL2 + s), (it / ST2_N) & 1);
                const uint32_t st = sbase + SM_PIPE + s * ST2_BYTES;
                wgmma_fence();
                #pragma unroll
                for (int kb2 = 0; kb2 < 2; kb2++)
                    #pragma unroll
                    for (int kk = 0; kk < 4; kk++)
                        wgmma_ss_n80(acc, desc_sw128(st + kb2 * 16384 + wg * 8192 + kk * 32, 16, 1024), desc_sw128(st + 32768 + kb2 * 10240 + kk * 32, 16, 1024));
                wgmma_commit();
                wgmma_wait<0>();
                if (wt == 0) mbar_arrive(BAR(B_EMPTY2 + s));
            }
            TSTAMP(5, tid == 0);
            mbar_wait(BAR(B_FULL2 + 0), (12 / ST2_N) & 1);
            mbar_wait(BAR(B_FULL2 + 1), (13 / ST2_N) & 1);
            TSTAMP(6, tid == 0);
            uint8_t* xn_t = smem + SM_PIPE;
            const uint8_t* q_t = smem + SM_PIPE + 20480;
            const uint32_t tT_t = sbase + SM_PIPE + ST2_BYTES + wg * 10240;
            uint32_t tw[20];
            {
                const int mi = lane >> 3, r = lane & 7;
                #pragma unroll
                for (int j2 = 0; j2 < 5; j2++) {
                    const int ch = 8 * (2 * j2 + (mi >> 1)) + r;
                    const int c = 2 * w + (mi & 1);
                    asm volatile("ldmatrix.sync.aligned.m8n8.x4.trans.shared.b16 {%0,%1,%2,%3}, [%4];"
                        : "=r"(tw[4 * j2]), "=r"(tw[4 * j2 + 1]), "=r"(tw[4 * j2 + 2]), "=r"(tw[4 * j2 + 3])
                        : "r"(tT_t + ch * 128 + ((c ^ (ch & 7)) << 4)));
                }
            }
            #pragma unroll
            for (int hh = 0; hh < 2; hh++) {
                const int row = 64 * wg + 16 * w + g + 8 * hh;
                uint32_t xw[10], qw[10], res[10];
                #pragma unroll
                for (int j = 0; j < 10; j++) {
                    xw[j] = *reinterpret_cast<const uint32_t*>(xn_t + row * 160 + (8 * j + 2 * q) * 2);
                    qw[j] = *reinterpret_cast<const uint32_t*>(q_t + row * 160 + (8 * j + 2 * q) * 2);
                }
                #pragma unroll
                for (int j = 0; j < 10; j++) {
                    const uint32_t tp = tw[2 * j + hh];
                    const uint32_t o2 = pack_bf2(acc[4 * j + 2 * hh], acc[4 * j + 2 * hh + 1]);
                    const float o0 = bflo(o2), o1 = bfhi(o2);
                    const uint32_t g2 = pack_bf2(__fdividef(o0, 1.0f + __expf(-o0)), __fdividef(o1, 1.0f + __expf(-o1)));
                    res[j] = badd2(qw[j], bmul2(bmul2(xw[j], tp), g2));
                }
                #pragma unroll
                for (int j = 0; j < 10; j++) *reinterpret_cast<uint32_t*>(xn_t + row * 160 + (8 * j + 2 * q) * 2) = res[j];
            }
            fence_proxy_async_smem();
            named_bar(2 + wg, 128);
            if (wt == 0) {
                tma_store_2d(&p.tm_out, sbase + SM_PIPE + wg * 64 * 160, ns * 80, tb * 128 + wg * 64);
                bulk_commit();
                bulk_wait_all();
            }
        }
    }
    __syncthreads();
    TSTAMP(7, tid == 0);
    if (tid == 0) {
        __threadfence();
        const unsigned dn = atomicAdd(&g_flags[FL_DONE * 32], 1u);
        if (dn == NCTA - 1) {
            for (int i = 0; i < NFLAGS; i++) g_flags[i * 32] = 0;
            __threadfence();
        }
    }
}

typedef CUresult (*PFN_encodeTiled)(CUtensorMap*, CUtensorMapDataType, cuuint32_t, void*, const cuuint64_t*, const cuuint64_t*, const cuuint32_t*, const cuuint32_t*,
                                    CUtensorMapInterleave, CUtensorMapSwizzle, CUtensorMapL2promotion, CUtensorMapFloatOOBfill);
static PFN_encodeTiled get_encode() {
    static PFN_encodeTiled fn = nullptr;
    if (!fn) {
        void* f = nullptr; cudaDriverEntryPointQueryResult qr;
        cudaGetDriverEntryPoint("cuTensorMapEncodeTiled", &f, cudaEnableDefault, &qr);
        fn = (PFN_encodeTiled)f;
    }
    return fn;
}
static void make_map(CUtensorMap* m, const void* base, int rank, const cuuint64_t* dims, const cuuint64_t* strides, const cuuint32_t* box, bool sw128) {
    cuuint32_t es[3] = {1, 1, 1};
    get_encode()(m, CU_TENSOR_MAP_DATA_TYPE_BFLOAT16, rank, const_cast<void*>(base), dims, strides, box, es, CU_TENSOR_MAP_INTERLEAVE_NONE,
                 sw128 ? CU_TENSOR_MAP_SWIZZLE_128B : CU_TENSOR_MAP_SWIZZLE_NONE, CU_TENSOR_MAP_L2_PROMOTION_L2_128B, CU_TENSOR_MAP_FLOAT_OOB_FILL_NONE);
}

}

extern "C" void kernel_launch(void* const* d_in, const int* in_sizes, int n_in, void* d_out, int out_size) {
    using namespace mk;
    Params p;
    p.q = (const __nv_bfloat16*)d_in[0]; p.k = (const __nv_bfloat16*)d_in[1]; p.v = (const __nv_bfloat16*)d_in[2];
    p.shift_k = (const __nv_bfloat16*)d_in[3]; p.ssm_k = (const __nv_bfloat16*)d_in[4]; p.ssm_D = (const __nv_bfloat16*)d_in[5];
    const __nv_bfloat16* w1 = (const __nv_bfloat16*)d_in[7];
    p.w2 = (const __nv_bfloat16*)d_in[8];
    p.out = (__nv_bfloat16*)d_out;
    void *xn, *w2T, *h, *tT;
    cudaGetSymbolAddress(&xn, g_xn); cudaGetSymbolAddress(&w2T, g_w2T); cudaGetSymbolAddress(&h, g_h); cudaGetSymbolAddress(&tT, g_tT);
    {
        cuuint64_t dims[2] = {640, 2048}, st[1] = {1280}; cuuint32_t box[2] = {64, 128};
        make_map(&p.tm_xn, xn, 2, dims, st, box, true);
    }
    {
        cuuint64_t dims[3] = {64, 640, 24}, st[2] = {3072, 128}; cuuint32_t box[3] = {64, 64, 3};
        make_map(&p.tm_w1, w1, 3, dims, st, box, true);
    }
    {
        cuuint64_t dims[2] = {1536, 2048}, st[1] = {3072}; cuuint32_t box[2] = {64, 64};
        make_map(&p.tm_hst, h, 2, dims, st, box, true);
    }
    {
        cuuint64_t dims[3] = {64, 2048, 24}, st[2] = {3072, 128}; cuuint32_t box[3] = {64, 128, 2};
        make_map(&p.tm_h, h, 3, dims, st, box, true);
    }
    {
        cuuint64_t dims[3] = {64, 640, 24}, st[2] = {3072, 128}; cuuint32_t box[3] = {64, 80, 2};
        make_map(&p.tm_w2T, w2T, 3, dims, st, box, true);
    }
    {
        cuuint64_t dims[2] = {640, 2048}, st[1] = {1280}; cuuint32_t box[2] = {80, 128};
        make_map(&p.tm_xn_e, xn, 2, dims, st, box, false);
        make_map(&p.tm_q_e, p.q, 2, dims, st, box, false);
        cuuint64_t dims2[2] = {2048, 640}, st2[1] = {4096}; cuuint32_t box2[2] = {64, 80};
        make_map(&p.tm_tT_e, tT, 2, dims2, st2, box2, true);
        cuuint32_t box3[2] = {80, 64};
        make_map(&p.tm_out, p.out, 2, dims, st, box3, false);
    }
    cudaFuncSetAttribute(mega_kernel, cudaFuncAttributeMaxDynamicSharedMemorySize, SM_TOTAL);
    mega_kernel<<<NCTA, NTHR, SM_TOTAL>>>(p);
}
```

```cpp
#include <cuda_runtime.h>
#include <cuda_bf16.h>
#include <cuda.h>
#include <stdint.h>

namespace mk {

constexpr int S_LEN = 2048, D_MODEL = 640, D_FF = 1536;
constexpr int NCTA = 128;
constexpr int NTHR = 384;
constexpr int CH_PER_CTA = 5;

__device__ __align__(1024) __nv_bfloat16 g_xn[S_LEN * D_MODEL];
__device__ __align__(1024) __nv_bfloat16 g_kvT[D_MODEL * S_LEN];
__device__ __align__(1024) __nv_bfloat16 g_w2T[D_MODEL * D_FF];
__device__ __align__(1024) __nv_bfloat16 g_h[S_LEN * D_FF];
__device__ __align__(1024) __nv_bfloat16 g_tT[D_MODEL * S_LEN];
constexpr int FL_XN = 0;
constexpr int FL_PREP = 16;
constexpr int FL_H = 17;
constexpr int FL_T = 33;
constexpr int FL_DONE = 41;
constexpr int FL_ERR = 42;
constexpr int FL_W2 = 43;
constexpr int NFLAGS = 44;
__device__ unsigned g_flags[NFLAGS * 32];

#define TSTAMP(i, cond) do {} while (0)
__device__ __forceinline__ uint32_t smem_u32(const void* p) { return (uint32_t)__cvta_generic_to_shared(p); }
__device__ __forceinline__ void mbar_init(uint32_t bar, uint32_t cnt) { asm volatile("mbarrier.init.shared::cta.b64 [%0], %1;" :: "r"(bar), "r"(cnt)); }
__device__ __forceinline__ void mbar_expect_tx(uint32_t bar, uint32_t bytes) { asm volatile("mbarrier.arrive.expect_tx.shared::cta.b64 _, [%0], %1;" :: "r"(bar), "r"(bytes) : "memory"); }
__device__ __forceinline__ void mbar_arrive(uint32_t bar) { asm volatile("mbarrier.arrive.shared::cta.b64 _, [%0];" :: "r"(bar) : "memory"); }
__device__ __forceinline__ void mbar_wait(uint32_t bar, uint32_t parity) {
    uint32_t ok; int it = 0;
    do {
        asm volatile("{\n.reg .pred p;\nmbarrier.try_wait.parity.shared::cta.b64 p, [%1], %2;\nselp.u32 %0, 1, 0, p;\n}\n" : "=r"(ok) : "r"(bar), "r"(parity) : "memory");
        if (++it > (1 << 22)) { g_flags[FL_ERR * 32] = 1; __trap(); }
    } while (!ok);
}
__device__ __forceinline__ void tma_load_2d(uint32_t dst, const CUtensorMap* map, int c0, int c1, uint32_t bar) {
    asm volatile("cp.async.bulk.tensor.2d.shared::cluster.global.mbarrier::complete_tx::bytes [%0], [%1, {%3, %4}], [%2];"
        :: "r"(dst), "l"(map), "r"(bar), "r"(c0), "r"(c1) : "memory");
}
__device__ __forceinline__ void tma_load_3d(uint32_t dst, const CUtensorMap* map, int c0, int c1, int c2, uint32_t bar) {
    asm volatile("cp.async.bulk.tensor.3d.shared::cluster.global.mbarrier::complete_tx::bytes [%0], [%1, {%3, %4, %5}], [%2];"
        :: "r"(dst), "l"(map), "r"(bar), "r"(c0), "r"(c1), "r"(c2) : "memory");
}
__device__ __forceinline__ void tma_store_2d(const CUtensorMap* map, uint32_t src, int c0, int c1) {
    asm volatile("cp.async.bulk.tensor.2d.global.shared::cta.bulk_group [%0, {%2, %3}], [%1];" :: "l"(map), "r"(src), "r"(c0), "r"(c1) : "memory");
}
__device__ __forceinline__ void bulk_commit() { asm volatile("cp.async.bulk.commit_group;" ::: "memory"); }
__device__ __forceinline__ void bulk_wait_all() { asm volatile("cp.async.bulk.wait_group 0;" ::: "memory"); }
__device__ __forceinline__ void fence_proxy_async() { asm volatile("fence.proxy.async;" ::: "memory"); }
__device__ __forceinline__ void fence_proxy_async_smem() { asm volatile("fence.proxy.async.shared::cta;" ::: "memory"); }
__device__ __forceinline__ void named_bar(int id, int n) { asm volatile("bar.sync %0, %1;" :: "r"(id), "r"(n) : "memory"); }
__device__ __forceinline__ void wgmma_fence() { asm volatile("wgmma.fence.sync.aligned;\n" ::: "memory"); }
__device__ __forceinline__ void wgmma_commit() { asm volatile("wgmma.commit_group.sync.aligned;\n" ::: "memory"); }
template<int N> __device__ __forceinline__ void wgmma_wait() { asm volatile("wgmma.wait_group.sync.aligned %0;\n" :: "n"(N) : "memory"); }
__device__ __forceinline__ unsigned ld_acquire(const unsigned* p) { unsigned v; asm volatile("ld.acquire.gpu.global.u32 %0, [%1];" : "=r"(v) : "l"(p) : "memory"); return v; }
__device__ __forceinline__ void wait_flag(int idx, unsigned target) {
    const unsigned* p = &g_flags[idx * 32];
    int it = 0;
    while (ld_acquire(p) < target) { if (++it > (1 << 22)) { g_flags[FL_ERR * 32] = 2; __trap(); } }
}
__device__ __forceinline__ void signal_flag(int idx) {
    __threadfence();
    atomicAdd(&g_flags[idx * 32], 1u);
}
__device__ __forceinline__ float bf2f(__nv_bfloat16 v) { return __bfloat162float(v); }
__device__ __forceinline__ float rbf(float x) { uint32_t r; asm("cvt.rn.bf16x2.f32 %0, %1, %2;" : "=r"(r) : "f"(0.f), "f"(x)); return __uint_as_float(r << 16); }
__device__ __forceinline__ uint32_t pack_bf2(float lo, float hi) { __nv_bfloat162 v = __floats2bfloat162_rn(lo, hi); return *reinterpret_cast<uint32_t*>(&v); }
__device__ __forceinline__ float bflo(uint32_t w) { return __uint_as_float(w << 16); }
__device__ __forceinline__ float bfhi(uint32_t w) { return __uint_as_float(w & 0xffff0000u); }

__device__ __forceinline__ uint32_t bmul2(uint32_t a, uint32_t b) { __nv_bfloat162 r = __hmul2_rn(*reinterpret_cast<__nv_bfloat162*>(&a), *reinterpret_cast<__nv_bfloat162*>(&b)); return *reinterpret_cast<uint32_t*>(&r); }
__device__ __forceinline__ uint32_t badd2(uint32_t a, uint32_t b) { __nv_bfloat162 r = __hadd2_rn(*reinterpret_cast<__nv_bfloat162*>(&a), *reinterpret_cast<__nv_bfloat162*>(&b)); return *reinterpret_cast<uint32_t*>(&r); }
__device__ __forceinline__ uint32_t bsub2(uint32_t a, uint32_t b) { __nv_bfloat162 r = __hsub2_rn(*reinterpret_cast<__nv_bfloat162*>(&a), *reinterpret_cast<__nv_bfloat162*>(&b)); return *reinterpret_cast<uint32_t*>(&r); }
__device__ __forceinline__ float div_by(float a, float d, float r) { float q = a * r; float e = fmaf(-q, d, a); return fmaf(e, r, q); }

__device__ __forceinline__ uint64_t desc_sw128(uint32_t addr, uint32_t lbo_bytes, uint32_t sbo_bytes) {
    return ((uint64_t)((addr & 0x3FFFF) >> 4)) | ((uint64_t)(lbo_bytes >> 4) << 16) | ((uint64_t)(sbo_bytes >> 4) << 32) | ((uint64_t)1 << 62);
}
__device__ __forceinline__ uint64_t desc_nosw(uint32_t addr, uint32_t lbo_bytes, uint32_t sbo_bytes) {
    return ((uint64_t)((addr & 0x3FFFF) >> 4)) | ((uint64_t)(lbo_bytes >> 4) << 16) | ((uint64_t)(sbo_bytes >> 4) << 32);
}

__device__ __forceinline__ void wgmma_rs_n8(float* d, uint32_t a0, uint32_t a1, uint32_t a2, uint32_t a3, uint64_t descB) {
    asm volatile("wgmma.mma_async.sync.aligned.m64n8k16.f32.bf16.bf16 {%0,%1,%2,%3}, {%4,%5,%6,%7}, %8, 1, 1, 1, 0;\n"
        : "+f"(d[0]), "+f"(d[1]), "+f"(d[2]), "+f"(d[3])
        : "r"(a0), "r"(a1), "r"(a2), "r"(a3), "l"(descB));
}
__device__ __forceinline__ void wgmma_rs_n16(float* d, uint32_t a0, uint32_t a1, uint32_t a2, uint32_t a3, uint64_t descB) {
    asm volatile("wgmma.mma_async.sync.aligned.m64n16k16.f32.bf16.bf16 {%0,%1,%2,%3,%4,%5,%6,%7}, {%8,%9,%10,%11}, %12, 1, 1, 1, 0;\n"
        : "+f"(d[0]), "+f"(d[1]), "+f"(d[2]), "+f"(d[3]), "+f"(d[4]), "+f"(d[5]), "+f"(d[6]), "+f"(d[7])
        : "r"(a0), "r"(a1), "r"(a2), "r"(a3), "l"(descB));
}
__device__ __forceinline__ void wgmma_rs_n24(float* d, uint32_t a0, uint32_t a1, uint32_t a2, uint32_t a3, uint64_t descB) {
    asm volatile("wgmma.mma_async.sync.aligned.m64n24k16.f32.bf16.bf16 {%0,%1,%2,%3,%4,%5,%6,%7,%8,%9,%10,%11}, {%12,%13,%14,%15}, %16, 1, 1, 1, 0;\n"
        : "+f"(d[0]), "+f"(d[1]), "+f"(d[2]), "+f"(d[3]), "+f"(d[4]), "+f"(d[5]), "+f"(d[6]), "+f"(d[7]), "+f"(d[8]), "+f"(d[9]), "+f"(d[10]), "+f"(d[11])
        : "r"(a0), "r"(a1), "r"(a2), "r"(a3), "l"(descB));
}
__device__ __forceinline__ void wgmma_rs_n32(float* d, uint32_t a0, uint32_t a1, uint32_t a2, uint32_t a3, uint64_t descB) {
    asm volatile("wgmma.mma_async.sync.aligned.m64n32k16.f32.bf16.bf16 {%0,%1,%2,%3,%4,%5,%6,%7,%8,%9,%10,%11,%12,%13,%14,%15}, {%16,%17,%18,%19}, %20, 1, 1, 1, 0;\n"
        : "+f"(d[0]), "+f"(d[1]), "+f"(d[2]), "+f"(d[3]), "+f"(d[4]), "+f"(d[5]), "+f"(d[6]), "+f"(d[7]), "+f"(d[8]), "+f"(d[9]), "+f"(d[10]), "+f"(d[11]), "+f"(d[12]), "+f"(d[13]), "+f"(d[14]), "+f"(d[15])
        : "r"(a0), "r"(a1), "r"(a2), "r"(a3), "l"(descB));
}
__device__ __forceinline__ void wgmma_rs_n48(float* d, uint32_t a0, uint32_t a1, uint32_t a2, uint32_t a3, uint64_t descB) {
    asm volatile("wgmma.mma_async.sync.aligned.m64n48k16.f32.bf16.bf16 {%0,%1,%2,%3,%4,%5,%6,%7,%8,%9,%10,%11,%12,%13,%14,%15,%16,%17,%18,%19,%20,%21,%22,%23}, {%24,%25,%26,%27}, %28, 1, 1, 1, 0;\n"
        : "+f"(d[0]), "+f"(d[1]), "+f"(d[2]), "+f"(d[3]), "+f"(d[4]), "+f"(d[5]), "+f"(d[6]), "+f"(d[7]), "+f"(d[8]), "+f"(d[9]), "+f"(d[10]), "+f"(d[11]), "+f"(d[12]), "+f"(d[13]), "+f"(d[14]), "+f"(d[15]), "+f"(d[16]), "+f"(d[17]), "+f"(d[18]), "+f"(d[19]), "+f"(d[20]), "+f"(d[21]), "+f"(d[22]), "+f"(d[23])
        : "r"(a0), "r"(a1), "r"(a2), "r"(a3), "l"(descB));
}
__device__ __forceinline__ void wgmma_rs_n64(float* d, uint32_t a0, uint32_t a1, uint32_t a2, uint32_t a3, uint64_t descB) {
    asm volatile("wgmma.mma_async.sync.aligned.m64n64k16.f32.bf16.bf16 {%0,%1,%2,%3,%4,%5,%6,%7,%8,%9,%10,%11,%12,%13,%14,%15,%16,%17,%18,%19,%20,%21,%22,%23,%24,%25,%26,%27,%28,%29,%30,%31}, {%32,%33,%34,%35}, %36, 1, 1, 1, 0;\n"
        : "+f"(d[0]), "+f"(d[1]), "+f"(d[2]), "+f"(d[3]), "+f"(d[4]), "+f"(d[5]), "+f"(d[6]), "+f"(d[7]), "+f"(d[8]), "+f"(d[9]), "+f"(d[10]), "+f"(d[11]), "+f"(d[12]), "+f"(d[13]), "+f"(d[14]), "+f"(d[15]), "+f"(d[16]), "+f"(d[17]), "+f"(d[18]), "+f"(d[19]), "+f"(d[20]), "+f"(d[21]), "+f"(d[22]), "+f"(d[23]), "+f"(d[24]), "+f"(d[25]), "+f"(d[26]), "+f"(d[27]), "+f"(d[28]), "+f"(d[29]), "+f"(d[30]), "+f"(d[31])
        : "r"(a0), "r"(a1), "r"(a2), "r"(a3), "l"(descB));
}
__device__ __forceinline__ void wgmma_ss_n192(float* d, uint64_t descA, uint64_t descB) {
    asm volatile("wgmma.mma_async.sync.aligned.m64n192k16.f32.bf16.bf16 {%0,%1,%2,%3,%4,%5,%6,%7,%8,%9,%10,%11,%12,%13,%14,%15,%16,%17,%18,%19,%20,%21,%22,%23,%24,%25,%26,%27,%28,%29,%30,%31,%32,%33,%34,%35,%36,%37,%38,%39,%40,%41,%42,%43,%44,%45,%46,%47,%48,%49,%50,%51,%52,%53,%54,%55,%56,%57,%58,%59,%60,%61,%62,%63,%64,%65,%66,%67,%68,%69,%70,%71,%72,%73,%74,%75,%76,%77,%78,%79,%80,%81,%82,%83,%84,%85,%86,%87,%88,%89,%90,%91,%92,%93,%94,%95}, %96, %97, 1, 1, 1, 0, 1;\n"
        : "+f"(d[0]), "+f"(d[1]), "+f"(d[2]), "+f"(d[3]), "+f"(d[4]), "+f"(d[5]), "+f"(d[6]), "+f"(d[7]), "+f"(d[8]), "+f"(d[9]), "+f"(d[10]), "+f"(d[11]), "+f"(d[12]), "+f"(d[13]), "+f"(d[14]), "+f"(d[15]), "+f"(d[16]), "+f"(d[17]), "+f"(d[18]), "+f"(d[19]), "+f"(d[20]), "+f"(d[21]), "+f"(d[22]), "+f"(d[23]), "+f"(d[24]), "+f"(d[25]), "+f"(d[26]), "+f"(d[27]), "+f"(d[28]), "+f"(d[29]), "+f"(d[30]), "+f"(d[31]), "+f"(d[32]), "+f"(d[33]), "+f"(d[34]), "+f"(d[35]), "+f"(d[36]), "+f"(d[37]), "+f"(d[38]), "+f"(d[39]), "+f"(d[40]), "+f"(d[41]), "+f"(d[42]), "+f"(d[43]), "+f"(d[44]), "+f"(d[45]), "+f"(d[46]), "+f"(d[47]), "+f"(d[48]), "+f"(d[49]), "+f"(d[50]), "+f"(d[51]), "+f"(d[52]), "+f"(d[53]), "+f"(d[54]), "+f"(d[55]), "+f"(d[56]), "+f"(d[57]), "+f"(d[58]), "+f"(d[59]), "+f"(d[60]), "+f"(d[61]), "+f"(d[62]), "+f"(d[63]), "+f"(d[64]), "+f"(d[65]), "+f"(d[66]), "+f"(d[67]), "+f"(d[68]), "+f"(d[69]), "+f"(d[70]), "+f"(d[71]), "+f"(d[72]), "+f"(d[73]), "+f"(d[74]), "+f"(d[75]), "+f"(d[76]), "+f"(d[77]), "+f"(d[78]), "+f"(d[79]), "+f"(d[80]), "+f"(d[81]), "+f"(d[82]), "+f"(d[83]), "+f"(d[84]), "+f"(d[85]), "+f"(d[86]), "+f"(d[87]), "+f"(d[88]), "+f"(d[89]), "+f"(d[90]), "+f"(d[91]), "+f"(d[92]), "+f"(d[93]), "+f"(d[94]), "+f"(d[95])
        : "l"(descA), "l"(descB));
}
__device__ __forceinline__ void wgmma_ss_n80(float* d, uint64_t descA, uint64_t descB) {
    asm volatile("wgmma.mma_async.sync.aligned.m64n80k16.f32.bf16.bf16 {%0,%1,%2,%3,%4,%5,%6,%7,%8,%9,%10,%11,%12,%13,%14,%15,%16,%17,%18,%19,%20,%21,%22,%23,%24,%25,%26,%27,%28,%29,%30,%31,%32,%33,%34,%35,%36,%37,%38,%39}, %40, %41, 1, 1, 1, 0, 0;\n"
        : "+f"(d[0]), "+f"(d[1]), "+f"(d[2]), "+f"(d[3]), "+f"(d[4]), "+f"(d[5]), "+f"(d[6]), "+f"(d[7]), "+f"(d[8]), "+f"(d[9]), "+f"(d[10]), "+f"(d[11]), "+f"(d[12]), "+f"(d[13]), "+f"(d[14]), "+f"(d[15]), "+f"(d[16]), "+f"(d[17]), "+f"(d[18]), "+f"(d[19]), "+f"(d[20]), "+f"(d[21]), "+f"(d[22]), "+f"(d[23]), "+f"(d[24]), "+f"(d[25]), "+f"(d[26]), "+f"(d[27]), "+f"(d[28]), "+f"(d[29]), "+f"(d[30]), "+f"(d[31]), "+f"(d[32]), "+f"(d[33]), "+f"(d[34]), "+f"(d[35]), "+f"(d[36]), "+f"(d[37]), "+f"(d[38]), "+f"(d[39])
        : "l"(descA), "l"(descB));
}
__device__ __forceinline__ void wgmma_ss_n64(float* d, uint64_t descA, uint64_t descB) {
    asm volatile("wgmma.mma_async.sync.aligned.m64n64k16.f32.bf16.bf16 {%0,%1,%2,%3,%4,%5,%6,%7,%8,%9,%10,%11,%12,%13,%14,%15,%16,%17,%18,%19,%20,%21,%22,%23,%24,%25,%26,%27,%28,%29,%30,%31}, %32, %33, 1, 1, 1, 0, 0;\n"
        : "+f"(d[0]), "+f"(d[1]), "+f"(d[2]), "+f"(d[3]), "+f"(d[4]), "+f"(d[5]), "+f"(d[6]), "+f"(d[7]), "+f"(d[8]), "+f"(d[9]), "+f"(d[10]), "+f"(d[11]), "+f"(d[12]), "+f"(d[13]), "+f"(d[14]), "+f"(d[15]), "+f"(d[16]), "+f"(d[17]), "+f"(d[18]), "+f"(d[19]), "+f"(d[20]), "+f"(d[21]), "+f"(d[22]), "+f"(d[23]), "+f"(d[24]), "+f"(d[25]), "+f"(d[26]), "+f"(d[27]), "+f"(d[28]), "+f"(d[29]), "+f"(d[30]), "+f"(d[31])
        : "l"(descA), "l"(descB));
}
__device__ __forceinline__ void wgmma_ss_n48(float* d, uint64_t descA, uint64_t descB) {
    asm volatile("wgmma.mma_async.sync.aligned.m64n48k16.f32.bf16.bf16 {%0,%1,%2,%3,%4,%5,%6,%7,%8,%9,%10,%11,%12,%13,%14,%15,%16,%17,%18,%19,%20,%21,%22,%23}, %24, %25, 1, 1, 1, 0, 0;\n"
        : "+f"(d[0]), "+f"(d[1]), "+f"(d[2]), "+f"(d[3]), "+f"(d[4]), "+f"(d[5]), "+f"(d[6]), "+f"(d[7]), "+f"(d[8]), "+f"(d[9]), "+f"(d[10]), "+f"(d[11]), "+f"(d[12]), "+f"(d[13]), "+f"(d[14]), "+f"(d[15]), "+f"(d[16]), "+f"(d[17]), "+f"(d[18]), "+f"(d[19]), "+f"(d[20]), "+f"(d[21]), "+f"(d[22]), "+f"(d[23])
        : "l"(descA), "l"(descB));
}
__device__ __forceinline__ void wgmma_ss_n32(float* d, uint64_t descA, uint64_t descB) {
    asm volatile("wgmma.mma_async.sync.aligned.m64n32k16.f32.bf16.bf16 {%0,%1,%2,%3,%4,%5,%6,%7,%8,%9,%10,%11,%12,%13,%14,%15}, %16, %17, 1, 1, 1, 0, 0;\n"
        : "+f"(d[0]), "+f"(d[1]), "+f"(d[2]), "+f"(d[3]), "+f"(d[4]), "+f"(d[5]), "+f"(d[6]), "+f"(d[7]), "+f"(d[8]), "+f"(d[9]), "+f"(d[10]), "+f"(d[11]), "+f"(d[12]), "+f"(d[13]), "+f"(d[14]), "+f"(d[15])
        : "l"(descA), "l"(descB));
}
__device__ __forceinline__ void wgmma_ss_n16(float* d, uint64_t descA, uint64_t descB) {
    asm volatile("wgmma.mma_async.sync.aligned.m64n16k16.f32.bf16.bf16 {%0,%1,%2,%3,%4,%5,%6,%7}, %8, %9, 1, 1, 1, 0, 0;\n"
        : "+f"(d[0]), "+f"(d[1]), "+f"(d[2]), "+f"(d[3]), "+f"(d[4]), "+f"(d[5]), "+f"(d[6]), "+f"(d[7])
        : "l"(descA), "l"(descB));
}

constexpr int SM_PIPE = 0;
constexpr int ST1_BYTES = 40960, ST1_N = 4;
constexpr int ST2_BYTES = 53248, ST2_N = 3;
constexpr int SM_CU = 2 * ST2_BYTES;
constexpr int SM_CT = SM_CU + 2 * 18432;
constexpr int SM_X = 163840;
constexpr int SM_U = SM_X;
constexpr int F_COPY1 = 4224 + 64;
constexpr int F_BYTES = F_COPY1 + 4224;
constexpr int SM_F = SM_X + 2 * 13824;
constexpr int SM_BAR = SM_F + 2 * F_BYTES;
constexpr int SM_RAW = SM_BAR + 256;
constexpr int RAW_BYTES = 4096 + 4096 + 1024 + 128;
constexpr int SM_TOTAL = SM_RAW + 2 * RAW_BYTES;
constexpr int B_FULL1 = 0, B_EMPTY1 = 4, B_FULL2 = 8, B_EMPTY2 = 11, B_G1DONE = 14, B_CONVDONE = 15, B_HSTG = 16, B_W2DONE = 18;

struct Params {
    CUtensorMap tm_xn, tm_w1, tm_hst, tm_h, tm_w2T, tm_xn_e, tm_q_e, tm_tT_e, tm_out;
    const __nv_bfloat16 *q, *k, *v, *shift_k, *ssm_k, *ssm_D, *w2;
    __nv_bfloat16* out;
};

#define SKIP_KV 0
#define SKIP_KVST 0
#define SKIP_W2 0
__device__ __forceinline__ void prep_w2T(const Params& p, uint8_t* smem, int cta, uint32_t bar_w2done) {
    const int lane = threadIdx.x & 31;
        const int k0 = (cta >> 3) * 96, n0 = (cta & 7) * 80;
        uint8_t* stg = smem + SM_U;
        #pragma unroll 1
        for (int bt = 0; bt < (SKIP_W2 ? 0 : 3); bt++) {
            uint4 vv[10];
            #pragma unroll
            for (int it = 0; it < 10; it++) {
                const int idx = lane + 32 * (bt * 10 + it);
                const int r = idx / 10, c = idx % 10;
                vv[it] = *reinterpret_cast<const uint4*>(p.w2 + (size_t)(k0 + r) * D_MODEL + n0 + c * 8);
            }
            #pragma unroll
            for (int it = 0; it < 10; it++) {
                const int idx = lane + 32 * (bt * 10 + it);
                const int r = idx / 10, c = idx % 10;
                uint32_t w[4] = {vv[it].x, vv[it].y, vv[it].z, vv[it].w};
                #pragma unroll
                for (int e = 0; e < 4; e++) {
                    *reinterpret_cast<uint16_t*>(stg + (c * 8 + 2 * e) * 208 + r * 2) = (uint16_t)(w[e] & 0xffffu);
                    *reinterpret_cast<uint16_t*>(stg + (c * 8 + 2 * e + 1) * 208 + r * 2) = (uint16_t)(w[e] >> 16);
                }
            }
        }
        __syncwarp();
        #pragma unroll 1
        for (int bt = 0; bt < (SKIP_W2 ? 0 : 3); bt++) {
            #pragma unroll
            for (int it = 0; it < 10; it++) {
                const int idx = lane + 32 * (bt * 10 + it);
                const int n = idx / 12, c = idx % 12;
                uint4 v4 = *reinterpret_cast<const uint4*>(stg + n * 208 + c * 16);
                *reinterpret_cast<uint4*>(g_w2T + (size_t)(n0 + n) * D_FF + k0 + c * 8) = v4;
            }
        }
        __syncwarp();
        if (lane == 0) { mbar_arrive(bar_w2done); __threadfence(); atomicAdd(&g_flags[FL_W2 * 32], 1u); }
}
__device__ __forceinline__ void prep_phase(const Params& p, uint8_t* smem, int cta) {
    const int tid = threadIdx.x, warp = tid >> 5, lane = tid & 31;
    const int s0 = cta * 16;
    if (warp < 8) {
        uint32_t w[2][10];
        #pragma unroll
        for (int rr = 0; rr < 2; rr++) {
            const __nv_bfloat16* xr = p.q + (size_t)(s0 + warp * 2 + rr) * D_MODEL;
            uint4 a = *reinterpret_cast<const uint4*>(xr + lane * 8);
            uint4 b = *reinterpret_cast<const uint4*>(xr + 256 + lane * 8);
            uint2 c = *reinterpret_cast<const uint2*>(xr + 512 + lane * 4);
            w[rr][0] = a.x; w[rr][1] = a.y; w[rr][2] = a.z; w[rr][3] = a.w; w[rr][4] = b.x; w[rr][5] = b.y; w[rr][6] = b.z; w[rr][7] = b.w; w[rr][8] = c.x; w[rr][9] = c.y;
        }
        #pragma unroll 1
        for (int rr = 0; rr < 2; rr++) {
            uint32_t wr[10];
            #pragma unroll
            for (int i = 0; i < 10; i++) wr[i] = rr ? w[1][i] : w[0][i];
            float x[20];
            #pragma unroll
            for (int i = 0; i < 10; i++) { x[2 * i] = bflo(wr[i]); x[2 * i + 1] = bfhi(wr[i]); }
            float sum = 0.f;
            #pragma unroll
            for (int i = 0; i < 20; i++) sum += x[i];
            #pragma unroll
            for (int o = 16; o > 0; o >>= 1) sum += __shfl_xor_sync(0xffffffffu, sum, o);
            const float mean = sum * (1.0f / 640.0f);
            float sq = 0.f;
            #pragma unroll
            for (int i = 0; i < 20; i++) { float dd = x[i] - mean; sq += dd * dd; }
            #pragma unroll
            for (int o = 16; o > 0; o >>= 1) sq += __shfl_xor_sync(0xffffffffu, sq, o);
            const float var_b = rbf(sq * (1.0f / 640.0f));
            const uint32_t m2 = pack_bf2(mean, mean);
            const float den = rbf(__fsqrt_rn(rbf(var_b + 1e-5f)));
            const float rden = __frcp_rn(den);
            uint32_t o[10];
            #pragma unroll
            for (int i = 0; i < 10; i++) {
                const uint32_t c2 = bsub2(wr[i], m2);
                o[i] = pack_bf2(div_by(bflo(c2), den, rden), div_by(bfhi(c2), den, rden));
            }
            __nv_bfloat16* yr = g_xn + (size_t)(s0 + warp * 2 + rr) * D_MODEL;
            *reinterpret_cast<uint4*>(yr + lane * 8) = make_uint4(o[0], o[1], o[2], o[3]);
            *reinterpret_cast<uint4*>(yr + 256 + lane * 8) = make_uint4(o[4], o[5], o[6], o[7]);
            *reinterpret_cast<uint2*>(yr + 512 + lane * 4) = make_uint2(o[8], o[9]);
        }
        named_bar(1, 256);
        if (tid == 0) { __threadfence(); atomicAdd(&g_flags[(FL_XN + (cta >> 3)) * 32], 1u); }
        __syncwarp();
        asm volatile("bar.arrive 5, 384;" ::: "memory");
    } else {
        const int t = tid - 256;
        const int half = t & 1;
        uint32_t kw[5][11], vw[5][8]; uint4 sk[5];
        #pragma unroll
        for (int it = 0; it < 5; it++) {
            const int d = 2 * ((t >> 1) + 64 * it);
            const int r0 = s0 + 8 * half;
            sk[it] = *reinterpret_cast<const uint4*>(p.shift_k + d * 4);
            #pragma unroll
            for (int j = 0; j < 11; j++) {
                const int row = r0 - 3 + j;
                kw[it][j] = (row >= 0) ? *reinterpret_cast<const uint32_t*>(p.k + (size_t)row * D_MODEL + d) : 0u;
            }
            #pragma unroll
            for (int j = 0; j < 8; j++) vw[it][j] = *reinterpret_cast<const uint32_t*>(p.v + (size_t)(r0 + j) * D_MODEL + d);
        }
        uint32_t o0[5][4], o1[5][4];
        #pragma unroll
        for (int it = 0; it < 5; it++) {
            const uint32_t W0 = __byte_perm(sk[it].x, sk[it].z, 0x5410), W1 = __byte_perm(sk[it].x, sk[it].z, 0x7632);
            const uint32_t W2 = __byte_perm(sk[it].y, sk[it].w, 0x5410), W3 = __byte_perm(sk[it].y, sk[it].w, 0x7632);
            uint32_t r[8];
            #pragma unroll
            for (int j = 0; j < 8; j++) {
                uint32_t a = bmul2(kw[it][j], W3);
                a = badd2(a, bmul2(kw[it][j + 1], W2));
                a = badd2(a, bmul2(kw[it][j + 2], W1));
                a = badd2(a, bmul2(kw[it][j + 3], W0));
                r[j] = bmul2(a, vw[it][j]);
            }
            #pragma unroll
            for (int j = 0; j < 4; j++) { o0[it][j] = __byte_perm(r[2 * j], r[2 * j + 1], 0x5410); o1[it][j] = __byte_perm(r[2 * j], r[2 * j + 1], 0x7632); }
        }
        named_bar(5, 384);
        #pragma unroll
        for (int it = 0; it < 5; it++) {
            const int d = 2 * ((t >> 1) + 64 * it);
            *reinterpret_cast<uint4*>(g_kvT + (size_t)d * S_LEN + s0 + 8 * half) = make_uint4(o0[it][0], o0[it][1], o0[it][2], o0[it][3]);
            *reinterpret_cast<uint4*>(g_kvT + (size_t)(d + 1) * S_LEN + s0 + 8 * half) = make_uint4(o1[it][0], o1[it][1], o1[it][2], o1[it][3]);
        }
        named_bar(3, 128);
        if (t == 0) { __threadfence(); atomicAdd(&g_flags[FL_PREP * 32], 1u); }
    }
}

__device__ __forceinline__ void stmatrix_x4(uint32_t addr, uint32_t r0, uint32_t r1, uint32_t r2, uint32_t r3) {
    asm volatile("stmatrix.sync.aligned.m8n8.x4.shared.b16 [%0], {%1, %2, %3, %4};" :: "r"(addr), "r"(r0), "r"(r1), "r"(r2), "r"(r3) : "memory");
}
__device__ __forceinline__ uint32_t lds32(uint32_t addr) { uint32_t v; asm volatile("ld.shared.u32 %0, [%1];" : "=r"(v) : "r"(addr)); return v; }

constexpr int UST = 1152;
constexpr int UCOPY = 4 * UST;
constexpr int UBUF = 4 * UCOPY;
template<int E>
__device__ __forceinline__ void conv_mma2(float* acc, const uint32_t (&A)[8], uint64_t descB) {
    #pragma unroll
    for (int kk = 0; kk < 2; kk++) {
        const uint64_t db = descB + (uint64_t)((2 * kk * UST) >> 4);
        if (E == 0) wgmma_rs_n64(acc, A[4 * kk], A[4 * kk + 1], A[4 * kk + 2], A[4 * kk + 3], db);
        if (E == 1) wgmma_rs_n48(acc, A[4 * kk], A[4 * kk + 1], A[4 * kk + 2], A[4 * kk + 3], db);
        if (E == 2) wgmma_rs_n32(acc, A[4 * kk], A[4 * kk + 1], A[4 * kk + 2], A[4 * kk + 3], db);
        if (E == 3) wgmma_rs_n16(acc, A[4 * kk], A[4 * kk + 1], A[4 * kk + 2], A[4 * kk + 3], db);
    }
}
__device__ __forceinline__ uint32_t swap16(uint32_t x) { uint32_t r; asm volatile("prmt.b32 %0, %1, 0, 0x1032;" : "=r"(r) : "r"(x)); return r; }
__device__ __forceinline__ void conv_ldP(uint32_t (&P)[5], uint32_t pfa, int s) {
    #pragma unroll
    for (int j = 0; j < 5; j++) P[j] = lds32(pfa + s * 128 + j * 16);
}
__device__ __forceinline__ void conv_mkA(uint32_t (&A)[8], const uint32_t (&P)[5]) {
    A[0] = swap16(P[3]); A[1] = swap16(P[4]); A[2] = swap16(P[2]); A[3] = swap16(P[3]);
    A[4] = swap16(P[1]); A[5] = swap16(P[2]); A[6] = swap16(P[0]); A[7] = swap16(P[1]);
}
__host__ __device__ constexpr int conv_step_of(int i) { return 8 * (i & 3) + (i >> 2); }
template<int I> struct ConvStep {
    __device__ static __forceinline__ void run(float* acc0, float* acc1, float* acc2, float* acc3, uint32_t (&A)[3][8], uint32_t (&P)[5], uint32_t pfa, uint32_t ubs) {
        if (I + 1 < 32) conv_mkA(A[(I + 1) % 3], P);
        if (I + 2 < 32) conv_ldP(P, pfa, conv_step_of(I + 2));
        constexpr int r = I >> 2;
        const uint64_t db = desc_nosw(ubs + (r & 3) * UCOPY + ((r >> 2) ? 0 : 128), UST, 128);
        wgmma_fence();
        if ((I & 3) == 0) conv_mma2<0>(acc0, A[I % 3], db);
        if ((I & 3) == 1) conv_mma2<1>(acc1, A[I % 3], db);
        if ((I & 3) == 2) conv_mma2<2>(acc2, A[I % 3], db);
        if ((I & 3) == 3) conv_mma2<3>(acc3, A[I % 3], db);
        wgmma_commit();
        wgmma_wait<1>();
        ConvStep<I + 1>::run(acc0, acc1, acc2, acc3, A, P, pfa, ubs);
    }
};
template<> struct ConvStep<32> { __device__ static __forceinline__ void run(float*, float*, float*, float*, uint32_t (&)[3][8], uint32_t (&)[5], uint32_t, uint32_t) {} };

#define EARLY_B 0
__global__ void __launch_bounds__(NTHR, 1) mega_kernel(const __grid_constant__ Params p) {
    extern __shared__ __align__(1024) uint8_t smem[];
    const int tid = threadIdx.x, warp = tid >> 5, lane = tid & 31;
    const int cta = blockIdx.x;
    const int tb = cta >> 3, ns = cta & 7;
    const uint32_t sbase = smem_u32(smem);
    const uint32_t bar0 = sbase + SM_BAR;
    #define BAR(i) (bar0 + (i) * 8)
    TSTAMP(15, tid == 0);

    if (tid == 0) {
        for (int i = 0; i < ST1_N; i++) { mbar_init(BAR(B_FULL1 + i), 1); mbar_init(BAR(B_EMPTY1 + i), 2); }
        for (int i = 0; i < ST2_N; i++) { mbar_init(BAR(B_FULL2 + i), 1); mbar_init(BAR(B_EMPTY2 + i), 2); }
        mbar_init(BAR(B_G1DONE), 1); mbar_init(BAR(B_CONVDONE), 2); mbar_init(BAR(B_HSTG), 1); mbar_init(BAR(B_W2DONE), 1); mbar_init(BAR(B_HSTG + 1), 1);
        asm volatile("fence.mbarrier_init.release.cluster;" ::: "memory");
    }
    __syncthreads();
    if (warp == 8) {
        const void* ptr = nullptr;
        switch (lane) {
            case 0: ptr = g_xn + (size_t)cta * 16 * D_MODEL; break;
            case 1: ptr = g_kvT + (size_t)cta * CH_PER_CTA * S_LEN; break;
            case 2: ptr = g_h + (size_t)(tb * 128) * D_FF + ns * 192; break;
            case 3: ptr = g_tT + (size_t)cta * CH_PER_CTA * S_LEN; break;
            case 4: ptr = g_w2T + (size_t)(ns * 80) * D_FF; break;
            case 5: ptr = g_flags; break;
            case 6: ptr = p.out + (size_t)(tb * 128) * D_MODEL; break;
            case 7: ptr = p.ssm_k + (size_t)cta * CH_PER_CTA * S_LEN; break;
            case 8: ptr = p.ssm_D; break;
            case 9: ptr = p.w2; break;
            default: break;
        }
        if (ptr) { uint32_t dummy; asm volatile("ld.global.u32 %0, [%1];" : "=r"(dummy) : "l"(ptr)); }
    }
    if (EARLY_B && warp == 8 && lane == 0) {
        for (int kb = 0; kb < ST1_N; kb++) {
            mbar_expect_tx(BAR(B_FULL1 + kb), ST1_BYTES);
            tma_load_3d(sbase + SM_PIPE + kb * ST1_BYTES + 16384, &p.tm_w1, 0, kb * 64, ns * 3, BAR(B_FULL1 + kb));
        }
    }
    prep_phase(p, smem, cta);
    if (warp == 9) prep_w2T(p, smem, cta, BAR(B_W2DONE));
    TSTAMP(0, tid == 0);

    if (warp >= 8) {
        if (warp == 9 && lane == 0) {
            #pragma unroll
            for (int hf = 0; hf < 2; hf++) {
                mbar_wait(BAR(B_HSTG + hf), 0);
                #pragma unroll
                for (int nb = 0; nb < 3; nb++)
                    tma_store_2d(&p.tm_hst, sbase + SM_PIPE + nb * 16384 + hf * 8192, ns * 192 + nb * 64, tb * 128 + hf * 64);
                bulk_commit();
            }
            bulk_wait_all();
            mbar_arrive(BAR(B_G1DONE));
            __threadfence();
            atomicAdd(&g_flags[(FL_H + tb) * 32], 2u);
        }
        if (warp == 8 && lane == 0) {
            for (int kb = ST1_N; kb < 10; kb++) {
                const int s = kb % ST1_N;
                if (kb >= ST1_N) mbar_wait(BAR(B_EMPTY1 + s), ((kb / ST1_N) - 1) & 1);
                const uint32_t st = sbase + SM_PIPE + s * ST1_BYTES;
                if (!EARLY_B || kb >= ST1_N) mbar_expect_tx(BAR(B_FULL1 + s), ST1_BYTES);
                tma_load_2d(st, &p.tm_xn, kb * 64, tb * 128, BAR(B_FULL1 + s));
                if (!EARLY_B || kb >= ST1_N) tma_load_3d(st + 16384, &p.tm_w1, 0, kb * 64, ns * 3, BAR(B_FULL1 + s));
            }
            mbar_wait(BAR(B_G1DONE), 0);
            wait_flag(FL_W2, NCTA);
            wait_flag(FL_H + tb, 16);
            fence_proxy_async();
            for (int it = 0; it < 12; it++) {
                const int s = it % ST2_N;
                if (it >= ST2_N) mbar_wait(BAR(B_EMPTY2 + s), ((it / ST2_N) - 1) & 1);
                if (it == 2) mbar_wait(BAR(B_CONVDONE), 0);
                const uint32_t st = sbase + SM_PIPE + s * ST2_BYTES;
                mbar_expect_tx(BAR(B_FULL2 + s), ST2_BYTES);
                tma_load_3d(st, &p.tm_h, 0, tb * 128, it * 2, BAR(B_FULL2 + s));
                tma_load_3d(st + 32768, &p.tm_w2T, 0, ns * 80, it * 2, BAR(B_FULL2 + s));
            }
            mbar_wait(BAR(B_EMPTY2 + 0), ((12 / ST2_N) - 1) & 1);
            mbar_expect_tx(BAR(B_FULL2 + 0), 2 * 20480);
            tma_load_2d(sbase + SM_PIPE, &p.tm_xn_e, ns * 80, tb * 128, BAR(B_FULL2 + 0));
            tma_load_2d(sbase + SM_PIPE + 20480, &p.tm_q_e, ns * 80, tb * 128, BAR(B_FULL2 + 0));
            mbar_wait(BAR(B_EMPTY2 + 1), ((13 / ST2_N) - 1) & 1);
            wait_flag(FL_T + ns, 16);
            fence_proxy_async();
            mbar_expect_tx(BAR(B_FULL2 + 1), 20480);
            tma_load_2d(sbase + SM_PIPE + ST2_BYTES, &p.tm_tT_e, tb * 128, ns * 80, BAR(B_FULL2 + 1));
            tma_load_2d(sbase + SM_PIPE + ST2_BYTES + 10240, &p.tm_tT_e, tb * 128 + 64, ns * 80, BAR(B_FULL2 + 1));
        }
    } else {
        const int wg = warp >> 2;
        const int w = warp & 3;
        const int wt = tid & 127;
        const int g = lane >> 2, q = lane & 3;
        const int d0 = cta * CH_PER_CTA;
        const uint32_t raw = sbase + SM_RAW + wg * RAW_BYTES;
        auto gload = [&](int d) {
            #pragma unroll
            for (int j = 0; j < 2; j++) {
                const int idx = wt + 128 * j;
                asm volatile("cp.async.cg.shared.global [%0], [%1], 16;" :: "r"(raw + idx * 16), "l"(g_kvT + (size_t)d * S_LEN + (idx & 63) * 32 + (idx >> 6) * 8) : "memory");
                asm volatile("cp.async.cg.shared.global [%0], [%1], 16;" :: "r"(raw + 4096 + idx * 16), "l"(p.ssm_k + (size_t)d * S_LEN + idx * 8) : "memory");
                asm volatile("cp.async.ca.shared.global [%0], [%1], 4;" :: "r"(raw + 8192 + idx * 4), "l"(p.ssm_k + (size_t)d * S_LEN + idx * 8 - (idx > 0 ? 2 : 0)) : "memory");
            }
            if (wt == 0) asm volatile("cp.async.ca.shared.global [%0], [%1], 4;" :: "r"(raw + 9216), "l"(p.ssm_D + (d & ~1)) : "memory");
            asm volatile("cp.async.commit_group;" ::: "memory");
        };
        if (tid == 0) {
            wait_flag(FL_XN + tb, 8);
            fence_proxy_async();
            for (int kb = 0; kb < ST1_N; kb++) {
                const uint32_t st = sbase + SM_PIPE + kb * ST1_BYTES;
                mbar_expect_tx(BAR(B_FULL1 + kb), ST1_BYTES);
                tma_load_2d(st, &p.tm_xn, kb * 64, tb * 128, BAR(B_FULL1 + kb));
                tma_load_3d(st + 16384, &p.tm_w1, 0, kb * 64, ns * 3, BAR(B_FULL1 + kb));
            }
        }
        __syncwarp();
        {
            float acc[96];
            #pragma unroll
            for (int i = 0; i < 96; i++) acc[i] = 0.f;
            for (int kb = 0; kb < 10; kb++) {
                const int s = kb % ST1_N;
                mbar_wait(BAR(B_FULL1 + s), (kb / ST1_N) & 1);
                const uint32_t sa = sbase + SM_PIPE + s * ST1_BYTES + wg * 8192;
                const uint32_t sb = sbase + SM_PIPE + s * ST1_BYTES + 16384;
                wgmma_fence();
                #pragma unroll
                for (int kk = 0; kk < 4; kk++)
                    wgmma_ss_n192(acc, desc_sw128(sa + kk * 32, 16, 1024), desc_sw128(sb + kk * 2048, 8192, 1024));
                wgmma_commit();
                if (kb == 6) { wait_flag(FL_PREP, NCTA); gload(d0 + wg); }
                wgmma_wait<0>();
                if (wt == 0) mbar_arrive(BAR(B_EMPTY1 + s));
            }
            TSTAMP(1, tid == 0);
            named_bar(1, 256);
            const uint32_t stg = sbase + SM_PIPE;
            const int m = lane >> 3, r = lane & 7;
            const int row = 16 * w + (m & 1) * 8 + r;
            #pragma unroll
            for (int j2 = 0; j2 < 12; j2++) {
                const int nb = j2 >> 2, cb = (2 * j2) & 7;
                uint32_t r0 = pack_bf2(fmaxf(acc[8 * j2 + 0], 0.f), fmaxf(acc[8 * j2 + 1], 0.f));
                uint32_t r1 = pack_bf2(fmaxf(acc[8 * j2 + 2], 0.f), fmaxf(acc[8 * j2 + 3], 0.f));
                uint32_t r2 = pack_bf2(fmaxf(acc[8 * j2 + 4], 0.f), fmaxf(acc[8 * j2 + 5], 0.f));
                uint32_t r3 = pack_bf2(fmaxf(acc[8 * j2 + 6], 0.f), fmaxf(acc[8 * j2 + 7], 0.f));
                const int chunk = cb + (m >> 1);
                stmatrix_x4(stg + nb * 16384 + wg * 8192 + row * 128 + ((chunk ^ (row & 7)) << 4), r0, r1, r2, r3);
            }
            fence_proxy_async_smem();
            named_bar(2 + wg, 128);
            if (wt == 0) mbar_arrive(BAR(B_HSTG + wg));
        }
        TSTAMP(2, tid == 0);
        {
            uint8_t* ub = smem + SM_CU + wg * UBUF;
            uint8_t* fb = smem + SM_F + wg * F_BYTES;
            float* X = reinterpret_cast<float*>(smem + SM_X + wg * 13824);
            uint8_t* Tst = smem + SM_CT + wg * 4096;
            named_bar(1, 256);
            for (int i = wt; i < 4 * 4 * 16; i += 128) {
                const int rho = i >> 6, st = (i >> 4) & 3, rr = i & 15;
                if (rr < 8 + 2 * rho) *reinterpret_cast<uint4*>(ub + rho * UCOPY + st * UST + rr * 16) = make_uint4(0, 0, 0, 0);
            }
            if (wt < 16) {
                const int cp = (wt >> 3) & 1, rr = wt & 7;
                *reinterpret_cast<uint4*>(fb + cp * F_COPY1 + rr * 16) = make_uint4(0, 0, 0, 0);
            }
            if (wt == 0) mbar_wait(BAR(B_W2DONE), 0);
            named_bar(2 + wg, 128);
            TSTAMP(3, tid == 0);
            const int nch = (wg == 0) ? 3 : 2;
            if (wg == 1) asm volatile("bar.arrive 6, 256;" ::: "memory");
            const uint32_t pf_off = (g & 1) ? (128 + 2 * (g - 1 - 2 * q)) : (F_COPY1 + 128 + 2 * (g - 2 * q));
            const uint32_t pfa = smem_u32(fb) + pf_off + 32 * w - 3 * 16;
            const uint32_t ubs = smem_u32(ub);
            for (int ci = 0; ci < nch; ci++) {
                const int d = d0 + 2 * ci + wg;
                asm volatile("cp.async.wait_group 0;" ::: "memory");
                if (wt == 0) { }
                #pragma unroll
                for (int j = 0; j < 2; j++) {
                    const int idx = wt + 128 * j;
                    const int a = idx & 63, kg = idx >> 6;
                    const uint4 pu = *reinterpret_cast<const uint4*>(smem + SM_RAW + wg * RAW_BYTES + idx * 16);
                    const uint4 pf = *reinterpret_cast<const uint4*>(smem + SM_RAW + wg * RAW_BYTES + 4096 + idx * 16);
                    const uint32_t pprev = (idx > 0) ? (*reinterpret_cast<const uint32_t*>(smem + SM_RAW + wg * RAW_BYTES + 8192 + idx * 4) >> 16) : 0u;
                    #pragma unroll
                    for (int rho = 0; rho < 4; rho++)
                        if (a + 8 + 2 * rho < 72) *reinterpret_cast<uint4*>(ub + rho * UCOPY + kg * UST + (a + 8 + 2 * rho) * 16) = pu;
                    *reinterpret_cast<uint4*>(fb + 128 + idx * 16) = pf;
                    *reinterpret_cast<uint4*>(fb + F_COPY1 + 128 + idx * 16) =
                        make_uint4(__byte_perm(pprev, pf.x, 0x5410), __byte_perm(pf.x, pf.y, 0x5432), __byte_perm(pf.y, pf.z, 0x5432), __byte_perm(pf.z, pf.w, 0x5432));
                }
                fence_proxy_async_smem();
                named_bar(2 + wg, 128);
                const float Dd = (d & 1) ? bfhi(*reinterpret_cast<const uint32_t*>(smem + SM_RAW + wg * RAW_BYTES + 9216)) : bflo(*reinterpret_cast<const uint32_t*>(smem + SM_RAW + wg * RAW_BYTES + 9216));
                named_bar(2 + wg, 128);
                if (ci + 1 < nch) gload(d + 2);

                float acc0[32], acc1[24], acc2[16], acc3[8];
                #pragma unroll
                for (int i = 0; i < 32; i++) acc0[i] = 0.f;
                #pragma unroll
                for (int i = 0; i < 24; i++) acc1[i] = 0.f;
                #pragma unroll
                for (int i = 0; i < 16; i++) acc2[i] = 0.f;
                #pragma unroll
                for (int i = 0; i < 8; i++) acc3[i] = 0.f;
                named_bar(6 + wg, 256);
                TSTAMP(8 + 2 * ci, tid == 0);

                {
                    uint32_t A[3][8], P[5];
                    conv_ldP(P, pfa, conv_step_of(0)); conv_mkA(A[0], P); conv_ldP(P, pfa, conv_step_of(1));
                    ConvStep<0>::run(acc0, acc1, acc2, acc3, A, P, pfa, ubs);
                    wgmma_wait<0>();
                }
                TSTAMP(9 + 2 * ci, tid == 0);
                if (!(wg == 0 && ci == 2)) asm volatile("bar.arrive %0, 256;" :: "r"(7 - wg) : "memory");
                #pragma unroll
                for (int i = 0; i < 32; i++) {
                    float v = acc0[i];
                    if (i >= 8) v += acc1[i - 8];
                    if (i >= 16) v += acc2[i - 16];
                    if (i >= 24) v += acc3[i - 24];
                    acc0[i] = v;
                }

                const int bl = 16 * (w & 1) + g;
                float* X1 = X;
                float* X0 = X + 64 * 36;
                if (w >= 2) {
                    #pragma unroll
                    for (int i = 0; i < 32; i++) { const int col = 8 * (i >> 2) + 2 * q + (i & 1); if (col < 63) X1[(col + 1) * 36 + bl + ((i >> 1) & 1) * 8] = acc0[i]; }
                } else {
                    #pragma unroll
                    for (int i = 16; i < 32; i++) X0[(8 * (i >> 2) + 2 * q + (i & 1) - 32) * 36 + bl + ((i >> 1) & 1) * 8] = acc0[i];
                }

                named_bar(2 + wg, 128);

                __nv_bfloat16* T = reinterpret_cast<__nv_bfloat16*>(Tst);
                float yv[16], uv[16];
                #pragma unroll
                for (int i = 0; i < 16; i++) {
                    const int b = bl + ((i >> 1) & 1) * 8;
                    const int a = 8 * (i >> 2) + 2 * q + (i & 1) + ((w < 2) ? 0 : 32);
                    if (w < 2) yv[i] = acc0[i] + ((a > 0) ? X1[a * 36 + b] : 0.f);
                    else yv[i] = X0[(a - 32) * 36 + b] + X1[a * 36 + b];
                    uv[i] = bf2f(*reinterpret_cast<const __nv_bfloat16*>(ub + (b >> 3) * UST + (a + 8) * 16 + (b & 7) * 2));
                }
                #pragma unroll
                for (int i = 0; i < 16; i++) {
                    const int b = bl + ((i >> 1) & 1) * 8;
                    const int a = 8 * (i >> 2) + 2 * q + (i & 1) + ((w < 2) ? 0 : 32);
                    T[32 * a + b] = __float2bfloat16_rn(rbf(yv[i]) + rbf(uv[i] * Dd));
                }

                named_bar(2 + wg, 128);

                #pragma unroll
                for (int j = 0; j < 2; j++)
                    *reinterpret_cast<uint4*>(g_tT + (size_t)d * S_LEN + (wt + 128 * j) * 8) = *reinterpret_cast<const uint4*>(Tst + (wt + 128 * j) * 16);

            }
            named_bar(1, 256);
            if (wt == 0) mbar_arrive(BAR(B_CONVDONE));
            if (tid == 0) signal_flag(FL_T + (cta >> 4));
        }
        TSTAMP(4, tid == 0);
        {
            float acc[40];
            #pragma unroll
            for (int i = 0; i < 40; i++) acc[i] = 0.f;
            for (int it = 0; it < 12; it++) {
                const int s = it % ST2_N;
                mbar_wait(BAR(B_FULL2 + s), (it / ST2_N) & 1);
                const uint32_t st = sbase + SM_PIPE + s * ST2_BYTES;
                wgmma_fence();
                #pragma unroll
                for (int kb2 = 0; kb2 < 2; kb2++)
                    #pragma unroll
                    for (int kk = 0; kk < 4; kk++)
                        wgmma_ss_n80(acc, desc_sw128(st + kb2 * 16384 + wg * 8192 + kk * 32, 16, 1024), desc_sw128(st + 32768 + kb2 * 10240 + kk * 32, 16, 1024));
                wgmma_commit();
                wgmma_wait<0>();
                if (wt == 0) mbar_arrive(BAR(B_EMPTY2 + s));
            }
            TSTAMP(5, tid == 0);
            mbar_wait(BAR(B_FULL2 + 0), (12 / ST2_N) & 1);
            mbar_wait(BAR(B_FULL2 + 1), (13 / ST2_N) & 1);
            TSTAMP(6, tid == 0);
            uint8_t* xn_t = smem + SM_PIPE;
            const uint8_t* q_t = smem + SM_PIPE + 20480;
            const uint32_t tT_t = sbase + SM_PIPE + ST2_BYTES + wg * 10240;
            uint32_t tw[20];
            {
                const int mi = lane >> 3, r = lane & 7;
                #pragma unroll
                for (int j2 = 0; j2 < 5; j2++) {
                    const int ch = 8 * (2 * j2 + (mi >> 1)) + r;
                    const int c = 2 * w + (mi & 1);
                    asm volatile("ldmatrix.sync.aligned.m8n8.x4.trans.shared.b16 {%0,%1,%2,%3}, [%4];"
                        : "=r"(tw[4 * j2]), "=r"(tw[4 * j2 + 1]), "=r"(tw[4 * j2 + 2]), "=r"(tw[4 * j2 + 3])
                        : "r"(tT_t + ch * 128 + ((c ^ (ch & 7)) << 4)));
                }
            }
            #pragma unroll
            for (int hh = 0; hh < 2; hh++) {
                const int row = 64 * wg + 16 * w + g + 8 * hh;
                uint32_t xw[10], qw[10], res[10];
                #pragma unroll
                for (int j = 0; j < 10; j++) {
                    xw[j] = *reinterpret_cast<const uint32_t*>(xn_t + row * 160 + (8 * j + 2 * q) * 2);
                    qw[j] = *reinterpret_cast<const uint32_t*>(q_t + row * 160 + (8 * j + 2 * q) * 2);
                }
                #pragma unroll
                for (int j = 0; j < 10; j++) {
                    const uint32_t tp = tw[2 * j + hh];
                    const uint32_t o2 = pack_bf2(acc[4 * j + 2 * hh], acc[4 * j + 2 * hh + 1]);
                    const float o0 = bflo(o2), o1 = bfhi(o2);
                    const uint32_t g2 = pack_bf2(__fdividef(o0, 1.0f + __expf(-o0)), __fdividef(o1, 1.0f + __expf(-o1)));
                    res[j] = badd2(qw[j], bmul2(bmul2(xw[j], tp), g2));
                }
                #pragma unroll
                for (int j = 0; j < 10; j++) *reinterpret_cast<uint32_t*>(xn_t + row * 160 + (8 * j + 2 * q) * 2) = res[j];
            }
            fence_proxy_async_smem();
            named_bar(2 + wg, 128);
            if (wt == 0) {
                tma_store_2d(&p.tm_out, sbase + SM_PIPE + wg * 64 * 160, ns * 80, tb * 128 + wg * 64);
                bulk_commit();
                bulk_wait_all();
            }
        }
    }
    __syncthreads();
    TSTAMP(7, tid == 0);
    if (tid == 0) {
        __threadfence();
        const unsigned dn = atomicAdd(&g_flags[FL_DONE * 32], 1u);
        if (dn == NCTA - 1) {
            for (int i = 0; i < NFLAGS; i++) g_flags[i * 32] = 0;
            __threadfence();
        }
    }
}

typedef CUresult (*PFN_encodeTiled)(CUtensorMap*, CUtensorMapDataType, cuuint32_t, void*, const cuuint64_t*, const cuuint64_t*, const cuuint32_t*, const cuuint32_t*,
                                    CUtensorMapInterleave, CUtensorMapSwizzle, CUtensorMapL2promotion, CUtensorMapFloatOOBfill);
static PFN_encodeTiled get_encode() {
    static PFN_encodeTiled fn = nullptr;
    if (!fn) {
        void* f = nullptr; cudaDriverEntryPointQueryResult qr;
        cudaGetDriverEntryPoint("cuTensorMapEncodeTiled", &f, cudaEnableDefault, &qr);
        fn = (PFN_encodeTiled)f;
    }
    return fn;
}
static void make_map(CUtensorMap* m, const void* base, int rank, const cuuint64_t* dims, const cuuint64_t* strides, const cuuint32_t* box, bool sw128) {
    cuuint32_t es[3] = {1, 1, 1};
    get_encode()(m, CU_TENSOR_MAP_DATA_TYPE_BFLOAT16, rank, const_cast<void*>(base), dims, strides, box, es, CU_TENSOR_MAP_INTERLEAVE_NONE,
                 sw128 ? CU_TENSOR_MAP_SWIZZLE_128B : CU_TENSOR_MAP_SWIZZLE_NONE, CU_TENSOR_MAP_L2_PROMOTION_L2_128B, CU_TENSOR_MAP_FLOAT_OOB_FILL_NONE);
}

}

extern "C" void kernel_launch(void* const* d_in, const int* in_sizes, int n_in, void* d_out, int out_size) {
    using namespace mk;
    Params p;
    p.q = (const __nv_bfloat16*)d_in[0]; p.k = (const __nv_bfloat16*)d_in[1]; p.v = (const __nv_bfloat16*)d_in[2];
    p.shift_k = (const __nv_bfloat16*)d_in[3]; p.ssm_k = (const __nv_bfloat16*)d_in[4]; p.ssm_D = (const __nv_bfloat16*)d_in[5];
    const __nv_bfloat16* w1 = (const __nv_bfloat16*)d_in[7];
    p.w2 = (const __nv_bfloat16*)d_in[8];
    p.out = (__nv_bfloat16*)d_out;
    void *xn, *w2T, *h, *tT;
    cudaGetSymbolAddress(&xn, g_xn); cudaGetSymbolAddress(&w2T, g_w2T); cudaGetSymbolAddress(&h, g_h); cudaGetSymbolAddress(&tT, g_tT);
    {
        cuuint64_t dims[2] = {640, 2048}, st[1] = {1280}; cuuint32_t box[2] = {64, 128};
        make_map(&p.tm_xn, xn, 2, dims, st, box, true);
    }
    {
        cuuint64_t dims[3] = {64, 640, 24}, st[2] = {3072, 128}; cuuint32_t box[3] = {64, 64, 3};
        make_map(&p.tm_w1, w1, 3, dims, st, box, true);
    }
    {
        cuuint64_t dims[2] = {1536, 2048}, st[1] = {3072}; cuuint32_t box[2] = {64, 64};
        make_map(&p.tm_hst, h, 2, dims, st, box, true);
    }
    {
        cuuint64_t dims[3] = {64, 2048, 24}, st[2] = {3072, 128}; cuuint32_t box[3] = {64, 128, 2};
        make_map(&p.tm_h, h, 3, dims, st, box, true);
    }
    {
        cuuint64_t dims[3] = {64, 640, 24}, st[2] = {3072, 128}; cuuint32_t box[3] = {64, 80, 2};
        make_map(&p.tm_w2T, w2T, 3, dims, st, box, true);
    }
    {
        cuuint64_t dims[2] = {640, 2048}, st[1] = {1280}; cuuint32_t box[2] = {80, 128};
        make_map(&p.tm_xn_e, xn, 2, dims, st, box, false);
        make_map(&p.tm_q_e, p.q, 2, dims, st, box, false);
        cuuint64_t dims2[2] = {2048, 640}, st2[1] = {4096}; cuuint32_t box2[2] = {64, 80};
        make_map(&p.tm_tT_e, tT, 2, dims2, st2, box2, true);
        cuuint32_t box3[2] = {80, 64};
        make_map(&p.tm_out, p.out, 2, dims, st, box3, false);
    }
    cudaFuncSetAttribute(mega_kernel, cudaFuncAttributeMaxDynamicSharedMemorySize, SM_TOTAL);
    mega_kernel<<<NCTA, NTHR, SM_TOTAL>>>(p);
}
```
